```python
import torch

def _softmax(x, axis=-1):
    return torch.softmax(x, dim=axis)
def _gelu(x):
    return torch.nn.functional.gelu(x, approximate="tanh")
def _silu(x):
    return torch.nn.functional.silu(x)
def _sigmoid(x):
    return torch.sigmoid(x)
def _layernorm(x, axis=-1, eps=1e-5):
    m = x.mean(dim=axis, keepdim=True)
    v = x.var(dim=axis, keepdim=True, unbiased=False)
    return (x - m) / torch.sqrt(v + eps)
def _scatter_add(tgt, idx, src, axis=0):
    return tgt.clone().index_add_(axis, idx, src)
def _segment_sum(src, seg, n):
    out = torch.zeros((n,) + src.shape[1:], dtype=src.dtype)
    return out.index_add_(0, seg, src)
def _pad(x, pw):
    flat = tuple(v for pair in reversed(pw) for v in pair)
    return torch.nn.functional.pad(x, flat)

kernel_name = 'standalone__gqa_block_cached__sampling'

def setup_inputs():

    _w = (lambda a: (lambda t: t.to(torch.bfloat16) if t.is_floating_point() else t)(torch.as_tensor(a)))
    B, Sq, D = 8, 4, 512
    Hq, Hkv, Sk, Dh = 32, 8, 2048, 128
    assert Hq % Hkv == 0, (Hq, Hkv)
    return {
        "x": _w((lambda *s: torch.randn(*s, dtype=torch.bfloat16) * 0.8)(B, Sq, D)),
        "k_cache": _w((lambda *s: torch.randn(*s, dtype=torch.bfloat16) * 0.8)(B, Hkv, Sk, Dh)),
        "v_cache": _w((lambda *s: torch.randn(*s, dtype=torch.bfloat16) * 0.05)(B, Hkv, Sk, Dh)),
        "wq": _w((lambda *s: torch.randn(*s, dtype=torch.bfloat16) * 0.8)(D, Hq * Dh) * (D ** -0.5)),
        "wo": _w((lambda *s: torch.randn(*s, dtype=torch.bfloat16) * 0.05)(Hq * Dh, D) * ((Hq * Dh) ** -0.5)),
    }

def reference(x, k_cache, v_cache, wq, wo):
    B, Sq, D = x.shape
    Hq, Dh = 32, 128
    Hkv = k_cache.shape[1]
    rep = Hq // Hkv
    q = (lambda x, *d: x.permute(*d))((x @ wq).reshape(B, Sq, Hq, Dh), 0, 2, 1, 3)
    k = (lambda x, n, axis: torch.repeat_interleave(x, n, dim=axis))(k_cache, rep, axis=1)
    v = (lambda x, n, axis: torch.repeat_interleave(x, n, dim=axis))(v_cache, rep, axis=1)
    scores = torch.einsum("bhqd,bhkd->bhqk", q, k) * (Dh ** -0.5)
    p = _softmax(scores, axis=-1)
    o = torch.einsum("bhqk,bhkd->bhqd", p, v)
    return (lambda x, *d: x.permute(*d))(o, 0, 2, 1, 3).reshape(B, Sq, Hq * Dh) @ wo
```

```cpp
#include <cuda_runtime.h>
#include <cuda.h>
#include <cuda_bf16.h>
#include <stdint.h>

namespace {

constexpr int NSTAGE = 10;
constexpr int STAGE_BYTES = 16384;
#define GQA_WINDOW 6
#define GQA_W0 2
#define GQA_W1 6
#define GQA_W1_UNTIL 8
#define GQA_PF_K 0
#define GQA_PF_WQ 1
#define GQA_TAU 645
#define GQA_T1 1600
#define GQA_FIRSTPOLL 2
#define GQA_START_TID 0
#define GQA_QDELAY 4000
#define GQA_PF_X 1
#define GQA_WQ_PROMO CU_TENSOR_MAP_L2_PROMOTION_L2_256B
#define GQA_KHINT 1
#define GQA_VHINT 1
constexpr int NTHREADS = 320;

constexpr int SM_RING = 0;
constexpr int SM_A = NSTAGE * STAGE_BYTES;
constexpr int SM_BAR = SM_A + 65536;
constexpr int SM_MX = SM_BAR + 256;
constexpr int SM_LS = SM_MX + 1024;
constexpr int SM_TOTAL = SM_LS + 1024;

constexpr int BAR_FULL = 0;
constexpr int BAR_EMPTY = BAR_FULL + 8 * 13;
constexpr int BAR_WO = BAR_EMPTY + 8 * NSTAGE;
constexpr int BAR_MX = BAR_WO + 32;
constexpr int BAR_P = BAR_MX + 8;
constexpr int BAR_OK = BAR_P + 8;
constexpr int BAR_WQ = BAR_OK + 8;
constexpr int BAR_AFREE = BAR_WQ + 8;
static_assert(BAR_AFREE + 8 <= 256, "barrier area");

__host__ __device__ constexpr int tile_seq(int n) { return n < 10 ? n : n - 3; }
__host__ __device__ constexpr int tile_slot(int n) { return (n >= 10 && n < 13) ? n : tile_seq(n) % NSTAGE; }
__host__ __device__ constexpr int tile_par(int n) { return (n >= 10 && n < 13) ? 0 : (tile_seq(n) / NSTAGE) & 1; }

constexpr int SPIN_LIMIT = 1 << 22;

struct Scratch {
    uint4 q[64 * 16 * 16];
    uint4 o[16 * 4 * 8 * 32];
    uint4 part[8 * 16 * 8 * 16 * 4];
    unsigned int cnt[32];
};
__device__ Scratch g_scratch;

#define PROF(slot)
constexpr int SM_EXTRA = 0;

__device__ __forceinline__ uint32_t smem_u32(const void* p) { return (uint32_t)__cvta_generic_to_shared(p); }
__device__ __forceinline__ void mbar_init(uint32_t bar, uint32_t count) {
    asm volatile("mbarrier.init.shared::cta.b64 [%0], %1;" :: "r"(bar), "r"(count) : "memory");
}
__device__ __forceinline__ void mbar_expect_tx(uint32_t bar, uint32_t bytes) {
    asm volatile("mbarrier.arrive.expect_tx.shared::cta.b64 _, [%0], %1;" :: "r"(bar), "r"(bytes) : "memory");
}
__device__ __forceinline__ void mbar_arrive(uint32_t bar) {
    asm volatile("mbarrier.arrive.shared::cta.b64 _, [%0];" :: "r"(bar) : "memory");
}
__device__ __forceinline__ void mbar_arrive_cluster(uint32_t bar_cluster_addr) {
    asm volatile("mbarrier.arrive.release.cluster.shared::cluster.b64 _, [%0];" :: "r"(bar_cluster_addr) : "memory");
}
__device__ __forceinline__ void mbar_wait(uint32_t bar, uint32_t parity) {
    uint32_t ok;
    int it = 0;
    do {
        asm volatile("{\n.reg .pred p;\nmbarrier.try_wait.parity.shared::cta.b64 p, [%1], %2;\nselp.u32 %0, 1, 0, p;\n}"
                     : "=r"(ok) : "r"(bar), "r"(parity) : "memory");
        if (++it > SPIN_LIMIT) __trap();
    } while (!ok);
}
__device__ __forceinline__ void mbar_wait_cluster(uint32_t bar, uint32_t parity) {
    uint32_t ok;
    int it = 0;
    do {
        asm volatile("{\n.reg .pred p;\nmbarrier.try_wait.parity.acquire.cluster.shared::cta.b64 p, [%1], %2;\nselp.u32 %0, 1, 0, p;\n}"
                     : "=r"(ok) : "r"(bar), "r"(parity) : "memory");
        if (++it > SPIN_LIMIT) __trap();
    } while (!ok);
}
__device__ __forceinline__ void tma3d(uint32_t dst, const CUtensorMap* tm, int c0, int c1, int c2, uint32_t bar) {
    asm volatile("cp.async.bulk.tensor.3d.shared::cluster.global.mbarrier::complete_tx::bytes [%0], [%1, {%3, %4, %5}], [%2];"
                 :: "r"(dst), "l"(tm), "r"(bar), "r"(c0), "r"(c1), "r"(c2) : "memory");
}
__device__ __forceinline__ void tma3d_hint(uint32_t dst, const CUtensorMap* tm, int c0, int c1, int c2, uint32_t bar, uint64_t pol) {
    asm volatile("cp.async.bulk.tensor.3d.shared::cluster.global.mbarrier::complete_tx::bytes.L2::cache_hint [%0], [%1, {%3, %4, %5}], [%2], %6;"
                 :: "r"(dst), "l"(tm), "r"(bar), "r"(c0), "r"(c1), "r"(c2), "l"(pol) : "memory");
}
__device__ __forceinline__ void cp_async16(uint32_t dst, const void* src) {
    asm volatile("cp.async.cg.shared.global [%0], [%1], 16;" :: "r"(dst), "l"(src) : "memory");
}
__device__ __forceinline__ uint4 ldg_nc(const void* p) {
    uint4 v;
    asm volatile("ld.global.nc.L1::no_allocate.v4.u32 {%0, %1, %2, %3}, [%4];" : "=r"(v.x), "=r"(v.y), "=r"(v.z), "=r"(v.w) : "l"(p));
    return v;
}
__device__ __forceinline__ void ldsm4(uint32_t (&r)[4], uint32_t addr) {
    asm volatile("ldmatrix.sync.aligned.m8n8.x4.shared.b16 {%0, %1, %2, %3}, [%4];"
                 : "=r"(r[0]), "=r"(r[1]), "=r"(r[2]), "=r"(r[3]) : "r"(addr) : "memory");
}
__device__ __forceinline__ void ldsm4t(uint32_t (&r)[4], uint32_t addr) {
    asm volatile("ldmatrix.sync.aligned.m8n8.x4.trans.shared.b16 {%0, %1, %2, %3}, [%4];"
                 : "=r"(r[0]), "=r"(r[1]), "=r"(r[2]), "=r"(r[3]) : "r"(addr) : "memory");
}
__device__ __forceinline__ void mma16816(float (&c)[4], uint32_t a0, uint32_t a1, uint32_t a2, uint32_t a3, uint32_t b0, uint32_t b1) {
    asm volatile("mma.sync.aligned.m16n8k16.row.col.f32.bf16.bf16.f32 {%0, %1, %2, %3}, {%4, %5, %6, %7}, {%8, %9}, {%0, %1, %2, %3};"
                 : "+f"(c[0]), "+f"(c[1]), "+f"(c[2]), "+f"(c[3]) : "r"(a0), "r"(a1), "r"(a2), "r"(a3), "r"(b0), "r"(b1));
}
__device__ __forceinline__ uint32_t pack_bf16(float lo, float hi) {
    uint32_t r;
    asm("cvt.rn.bf16x2.f32 %0, %1, %2;" : "=r"(r) : "f"(hi), "f"(lo));
    return r;
}
__device__ __forceinline__ float ex2(float x) {
    float r;
    asm("ex2.approx.ftz.f32 %0, %1;" : "=f"(r) : "f"(x));
    return r;
}
__device__ __forceinline__ uint4 ld_relaxed_v4(const uint4* p) {
    uint4 v;
    asm volatile("ld.relaxed.gpu.global.v4.u32 {%0, %1, %2, %3}, [%4];" : "=r"(v.x), "=r"(v.y), "=r"(v.z), "=r"(v.w) : "l"(p) : "memory");
    return v;
}
__device__ __forceinline__ void st_relaxed_v2(void* p, uint32_t a, uint32_t b) {
    asm volatile("st.relaxed.gpu.global.v2.u32 [%0], {%1, %2};" :: "l"(p), "r"(a), "r"(b) : "memory");
}
__device__ __forceinline__ uint32_t nz(uint32_t w) { return w == 0u ? 0x80000000u : w; }
__device__ __forceinline__ bool valid4(const uint4& v) { return v.x != 0u && v.y != 0u && v.z != 0u && v.w != 0u; }
__device__ __forceinline__ void bar_compute() { asm volatile("bar.sync 1, 256;" ::: "memory"); }

__device__ __forceinline__ void arrive_and_wait(unsigned int* cnt, unsigned int n) {
    unsigned int old;
    asm volatile("atom.add.release.gpu.global.u32 %0, [%1], 1;" : "=r"(old) : "l"(cnt) : "memory");
    const unsigned int target = (old | (n - 1)) + 1;
    unsigned int cur;
    int it = 0;
    do {
        asm volatile("ld.acquire.gpu.global.u32 %0, [%1];" : "=r"(cur) : "l"(cnt) : "memory");
        if (++it > SPIN_LIMIT) __trap();
    } while ((int)(cur - target) < 0);
}

__global__ void __cluster_dims__(2, 1, 1) __launch_bounds__(NTHREADS, 1)
gqa_fused_kernel(const __nv_bfloat16* __restrict__ wq, const __nv_bfloat16* __restrict__ x, __nv_bfloat16* __restrict__ out,
                 Scratch* __restrict__ scr, const __nv_bfloat16* __restrict__ kc,
                 const __grid_constant__ CUtensorMap tmK, const __grid_constant__ CUtensorMap tmV,
                 const __grid_constant__ CUtensorMap tmWo, const __grid_constant__ CUtensorMap tmWq,
                 const __grid_constant__ CUtensorMap tmX) {
    extern __shared__ __align__(1024) unsigned char smem[];
    const int tid = threadIdx.x;
    uint4* const g_q = scr->q;
    uint4* const g_o = scr->o;
    uint4* const g_part = scr->part;
    unsigned int* const g_cnt = scr->cnt;
    const uint32_t sb = smem_u32(smem);
    const uint32_t bars = sb + SM_BAR;
    const int warp = tid >> 5, lane = tid & 31;
    const int r = blockIdx.x & 1;
    const int pair = blockIdx.x >> 1;
    const int b = pair >> 3, hkv = pair & 7;
    const int krow = blockIdx.x * 1024;
    uint64_t pol;
    asm volatile("createpolicy.fractional.L2::evict_first.b64 %0, 1.0;" : "=l"(pol));
    uint32_t t_start;
    asm volatile("mov.u32 %0, %%globaltimer_lo;" : "=r"(t_start));

    if (tid == GQA_START_TID) {
        PROF(21);
        if (GQA_PF_X) asm volatile("cp.async.bulk.prefetch.L2.global [%0], %1;" :: "l"(x + blockIdx.x * 128), "r"(256) : "memory");
        if (GQA_PF_WQ) asm volatile("cp.async.bulk.prefetch.L2.global [%0], %1;" :: "l"(wq + blockIdx.x * 16384), "r"(32768) : "memory");
        PROF(26);
        mbar_init(bars + BAR_WQ, 1);
#pragma unroll
        for (int n = 0; n < GQA_W0; n++) mbar_init(bars + BAR_FULL + 8 * n, 1);
        asm volatile("fence.proxy.async.shared::cta;" ::: "memory");
        PROF(27);
        mbar_expect_tx(bars + BAR_WQ, 65536);
        tma3d(sb + 8 * STAGE_BYTES, &tmX, 0, 0, 0, bars + BAR_WQ);
        tma3d(sb + SM_A, &tmWq, hkv * 512 + (b * 2 + r) * 32, 0, 0, bars + BAR_WQ);
        PROF(28);
#pragma unroll
        for (int n = 0; n < GQA_W0; n++) {
            mbar_expect_tx(bars + BAR_FULL + 8 * n, STAGE_BYTES);
            if (GQA_KHINT) tma3d_hint(sb + n * STAGE_BYTES, &tmK, 0, krow + n * 64, 0, bars + BAR_FULL + 8 * n, pol);
            else tma3d(sb + n * STAGE_BYTES, &tmK, 0, krow + n * 64, 0, bars + BAR_FULL + 8 * n);
        }
        PROF(25);
#pragma unroll
        for (int off = 8 * GQA_W0; off <= BAR_AFREE; off += 8)
            if (off != BAR_WQ) mbar_init(bars + off, off < BAR_EMPTY ? 1 : off < BAR_WO ? 8 : off < BAR_MX ? 1 : off < BAR_OK ? 9 : 1);
        mbar_expect_tx(bars + BAR_MX, 512);
        mbar_expect_tx(bars + BAR_P, 32768 + 512);
        asm volatile("fence.mbarrier_init.release.cluster;" ::: "memory");
        asm volatile("fence.proxy.async.shared::cta;" ::: "memory");
        PROF(29);
    }
    __syncwarp();
    asm volatile("barrier.cluster.arrive.relaxed.aligned;" ::: "memory");
    __syncthreads();

    if (warp == 8) {
        if (lane == 0) {
            asm volatile("prefetch.tensormap [%0];" :: "l"(&tmV) : "memory");
            asm volatile("prefetch.tensormap [%0];" :: "l"(&tmWo) : "memory");
            uint32_t due = t_start + GQA_T1;
#pragma unroll 1
            for (int n = GQA_W0; n < 34; n++) {
                {
                    uint32_t now;
                    do { asm volatile("mov.u32 %0, %%globaltimer_lo;" : "=r"(now)); } while ((int)(now - due) < 0);
                    due += GQA_TAU;
                }
                const int W = n < GQA_W1_UNTIL ? GQA_W1 : GQA_WINDOW;
                if (n >= W) mbar_wait(bars + BAR_FULL + 8 * tile_slot(n - W), tile_par(n - W));
                const int s = tile_slot(n);
                if (n == 8) mbar_wait(bars + BAR_AFREE, 0);
                if (n >= 13) mbar_wait(bars + BAR_EMPTY + 8 * s, tile_par(n) ^ 1);
                const uint32_t dst = sb + s * STAGE_BYTES;
                if (n < 32) {
                    const uint32_t fb = bars + BAR_FULL + 8 * s;
                    mbar_expect_tx(fb, STAGE_BYTES);
                    if (n < 16) {
                        if (GQA_KHINT) tma3d_hint(dst, &tmK, 0, krow + n * 64, 0, fb, pol);
                        else tma3d(dst, &tmK, 0, krow + n * 64, 0, fb);
                    } else {
                        if (GQA_VHINT) tma3d_hint(dst, &tmV, 0, pair * 2048 + (n - 16) * 128, r, fb, pol);
                        else tma3d(dst, &tmV, 0, pair * 2048 + (n - 16) * 128, r, fb);
                    }
                    PROF(64 + n);
                } else {
#pragma unroll
                    for (int h = 0; h < 2; h++) {
                        const int qd = (n - 32) * 2 + h;
                        mbar_expect_tx(bars + BAR_WO + 8 * qd, 8192);
                        tma3d(dst + h * 8192, &tmWo, b * 64, r * 64 + qd * 16, hkv * 4, bars + BAR_WO + 8 * qd);
                    }
                }
            }
        }
        __syncwarp();
        asm volatile("barrier.cluster.wait.acquire.aligned;" ::: "memory");
    } else if (warp == 9) {
        if (lane == 0) PROF(19);
        mbar_wait(bars + BAR_AFREE, 0);
        const uint4 z = make_uint4(0u, 0u, 0u, 0u);
#pragma unroll 1
        for (int i = 0; i < 4; i++) g_o[blockIdx.x * 128 + i * 32 + lane] = z;
#pragma unroll 4
        for (int i = 0; i < 16; i++) g_part[blockIdx.x * 512 + i * 32 + lane] = z;
        __syncwarp();
        if (lane == 0) {
            arrive_and_wait(&g_cnt[0], 128);
            mbar_arrive(bars + BAR_OK);
            PROF(20);
        }
        __syncwarp();
        asm volatile("barrier.cluster.wait.acquire.aligned;" ::: "memory");
    } else {
        const int g = lane >> 2, t = lane & 3;
        const int mi = lane >> 3, r8 = lane & 7;
        const uint32_t ws = sb + SM_A;
        mbar_wait(bars + BAR_WQ, 0);
        if (tid == 0) PROF(1);

        {
            float acc[4][4];
#pragma unroll
            for (int nt = 0; nt < 4; nt++) { acc[nt][0] = acc[nt][1] = acc[nt][2] = acc[nt][3] = 0.f; }
            const uint32_t wa = ws + ((warp >> 1) * 128 + lane) * 64;
            const uint32_t xa = sb + 8 * STAGE_BYTES + (warp >> 1) * 8192 + ((warp & 1) * 16 + (mi & 1) * 8 + r8) * 128;
#pragma unroll
            for (int i = 0; i < 4; i++) {
                uint32_t a0[4], a1[4];
                ldsm4(a0, xa + (i >> 1) * 4096 + ((((i & 1) * 4 + (mi >> 1)) ^ r8) << 4));
                ldsm4(a1, xa + (i >> 1) * 4096 + ((((i & 1) * 4 + 2 + (mi >> 1)) ^ r8) << 4));
#pragma unroll
                for (int nt = 0; nt < 4; nt++) {
                    uint32_t bw[4];
                    ldsm4t(bw, wa + i * 2048 + ((nt ^ (r8 >> 1)) << 4));
                    mma16816(acc[nt], a0[0], a0[1], a0[2], a0[3], bw[0], bw[1]);
                    mma16816(acc[nt], a1[0], a1[1], a1[2], a1[3], bw[2], bw[3]);
                }
            }
            if (tid == 0) PROF(24);
            float4* red = reinterpret_cast<float4*>(smem + SM_A + 32768);
#pragma unroll
            for (int hf = 0; hf < 2; hf++) {
                const int idx = (warp >> 1) * 256 + ((warp & 1) * 16 + hf * 8 + g) * 4 + t;
                red[idx] = make_float4(acc[0][2 * hf], acc[0][2 * hf + 1], acc[1][2 * hf], acc[1][2 * hf + 1]);
                red[idx + 128] = make_float4(acc[2][2 * hf], acc[2][2 * hf + 1], acc[3][2 * hf], acc[3][2 * hf + 1]);
            }
            bar_compute();
            if (tid < 128) {
                uint32_t w[4];
#pragma unroll
                for (int hf = 0; hf < 2; hf++) {
                    const float4 v0 = red[hf * 128 + tid], v1 = red[256 + hf * 128 + tid], v2 = red[512 + hf * 128 + tid], v3 = red[768 + hf * 128 + tid];
                    w[2 * hf] = nz(pack_bf16((v0.x + v1.x) + (v2.x + v3.x), (v0.y + v1.y) + (v2.y + v3.y)));
                    w[2 * hf + 1] = nz(pack_bf16((v0.z + v1.z) + (v2.z + v3.z), (v0.w + v1.w) + (v2.w + v3.w)));
                }
                uint4* dst = &g_q[(((tid >> 4) * 8 + hkv) * 16 + b * 2 + r) * 16 + (tid & 15)];
                asm volatile("st.relaxed.gpu.global.v4.u32 [%0], {%1, %2, %3, %4};" :: "l"(dst), "r"(w[0]), "r"(w[1]), "r"(w[2]), "r"(w[3]) : "memory");
            }
        }
        if (tid == 0) PROF(2);
        uint4 qf[8];
        {
            const uint4* qsrc = &g_q[pair * 256 + tid];
            bar_compute();
            if (tid == 0) mbar_arrive(bars + BAR_AFREE);
            { long long t0 = clock64(); while (clock64() - t0 < GQA_QDELAY) {} }
            uint4 w = ld_relaxed_v4(qsrc);
            int it = 0;
            while (!valid4(w)) {
                w = ld_relaxed_v4(qsrc);
                if (++it > SPIN_LIMIT) __trap();
            }
            uint4* qs = reinterpret_cast<uint4*>(smem + SM_A + 49152);
            qs[tid] = w;
            bar_compute();
#pragma unroll
            for (int i = 0; i < 8; i++) qf[i] = qs[((g >> 2) * 4 + (i & 1) * 8 + (i >> 1)) * 16 + (g & 3) * 4 + t];
        }
        if (tid == 0) PROF(3);

        float S[16][4];
        {
            const uint32_t ka = sb + SM_RING + (warp * 8 + r8) * 128;
#pragma unroll
            for (int n = 0; n < 16; n++) {
                const int s = tile_slot(n);
                mbar_wait(bars + BAR_FULL + 8 * s, tile_par(n));
                float e[4] = {0.f, 0.f, 0.f, 0.f}, o[4] = {0.f, 0.f, 0.f, 0.f};
#pragma unroll
                for (int i = 0; i < 4; i++) {
                    uint32_t kf[4];
                    ldsm4(kf, ka + s * STAGE_BYTES + (i >> 1) * 8192 + (((((i & 1) << 2) + mi) ^ r8) << 4));
                    mma16816(e, qf[2 * i].x, qf[2 * i + 1].x, qf[2 * i].y, qf[2 * i + 1].y, kf[0], kf[1]);
                    mma16816(o, qf[2 * i].z, qf[2 * i + 1].z, qf[2 * i].w, qf[2 * i + 1].w, kf[2], kf[3]);
                }
#pragma unroll
                for (int i = 0; i < 4; i++) S[n][i] = e[i] + o[i];
                if (s < NSTAGE) {
                    __syncwarp();
                    if (lane == 0) mbar_arrive(bars + BAR_EMPTY + 8 * s);
                }
                if (tid == 0) PROF(32 + n);
            }
        }
        if (tid == 0) PROF(5);

        asm volatile("barrier.cluster.wait.acquire.aligned;" ::: "memory");
        uint32_t peer;
        asm("mapa.shared::cluster.u32 %0, %1, %2;" : "=r"(peer) : "r"(sb), "r"(r ^ 1));
        float inv0, inv1;
        {
            float m0 = fmaxf(S[0][0], S[0][1]), m1 = fmaxf(S[0][2], S[0][3]);
#pragma unroll
            for (int n = 1; n < 16; n++) { m0 = fmaxf(m0, fmaxf(S[n][0], S[n][1])); m1 = fmaxf(m1, fmaxf(S[n][2], S[n][3])); }
            m0 = fmaxf(m0, __shfl_xor_sync(0xffffffffu, m0, 1)); m1 = fmaxf(m1, __shfl_xor_sync(0xffffffffu, m1, 1));
            m0 = fmaxf(m0, __shfl_xor_sync(0xffffffffu, m0, 2)); m1 = fmaxf(m1, __shfl_xor_sync(0xffffffffu, m1, 2));
            const uint32_t off = (uint32_t)(((t & 1) * 8 + g) * 16 + r * 8 + warp) * 4;
            const float mv = (t & 1) ? m1 : m0;
            if (t & 2) asm volatile("st.async.shared::cluster.mbarrier::complete_tx::bytes.f32 [%0], %1, [%2];" :: "r"(peer + SM_MX + off), "f"(mv), "r"(peer + SM_BAR + BAR_MX) : "memory");
            else asm volatile("st.shared.f32 [%0], %1;" :: "r"(sb + SM_MX + off), "f"(mv) : "memory");
            __syncwarp();
            if (lane == 0) mbar_arrive(bars + BAR_MX);
            mbar_wait_cluster(bars + BAR_MX, 0);
            if (tid == 0) PROF(14);
            if (tid < 128) g_q[pair * 256 + r * 128 + tid] = make_uint4(0u, 0u, 0u, 0u);
            const float4* mx = reinterpret_cast<const float4*>(smem + SM_MX);
            const float4 u0 = mx[g * 4 + t], u1 = mx[(g + 8) * 4 + t];
            m0 = fmaxf(fmaxf(u0.x, u0.y), fmaxf(u0.z, u0.w));
            m1 = fmaxf(fmaxf(u1.x, u1.y), fmaxf(u1.z, u1.w));
            m0 = fmaxf(m0, __shfl_xor_sync(0xffffffffu, m0, 1)); m1 = fmaxf(m1, __shfl_xor_sync(0xffffffffu, m1, 1));
            m0 = fmaxf(m0, __shfl_xor_sync(0xffffffffu, m0, 2)); m1 = fmaxf(m1, __shfl_xor_sync(0xffffffffu, m1, 2));
            const float c = 0.08838834764831845f * 1.4426950408889634f;
            float l0 = 0.f, l1 = 0.f;
            const uint32_t poff = SM_A + (r * 8 + warp) * 4096 + lane * 16;
#pragma unroll
            for (int u = 0; u < 8; u++) {
                float p[8];
#pragma unroll
                for (int i = 0; i < 8; i++) p[i] = ex2((S[2 * u + (i >> 2)][i & 3] - ((i & 2) ? m1 : m0)) * c);
                l0 += (p[0] + p[1]) + (p[4] + p[5]);
                l1 += (p[2] + p[3]) + (p[6] + p[7]);
                const uint32_t a0 = pack_bf16(p[0], p[1]), a1 = pack_bf16(p[2], p[3]), a2 = pack_bf16(p[4], p[5]), a3 = pack_bf16(p[6], p[7]);
                asm volatile("st.shared.v4.u32 [%0], {%1, %2, %3, %4};" :: "r"(sb + poff + u * 512), "r"(a0), "r"(a1), "r"(a2), "r"(a3) : "memory");
            }
            asm volatile("fence.proxy.async.shared::cta;" ::: "memory");
            __syncwarp();
            if (lane == 0)
                asm volatile("cp.async.bulk.shared::cluster.shared::cta.mbarrier::complete_tx::bytes [%0], [%1], %2, [%3];"
                             :: "r"(peer + poff), "r"(sb + poff), "r"(4096), "r"(peer + SM_BAR + BAR_P) : "memory");
            l0 += __shfl_xor_sync(0xffffffffu, l0, 1); l1 += __shfl_xor_sync(0xffffffffu, l1, 1);
            l0 += __shfl_xor_sync(0xffffffffu, l0, 2); l1 += __shfl_xor_sync(0xffffffffu, l1, 2);
            const float lv = (t & 1) ? l1 : l0;
            if (t & 2) asm volatile("st.async.shared::cluster.mbarrier::complete_tx::bytes.f32 [%0], %1, [%2];" :: "r"(peer + SM_LS + off), "f"(lv), "r"(peer + SM_BAR + BAR_P) : "memory");
            else asm volatile("st.shared.f32 [%0], %1;" :: "r"(sb + SM_LS + off), "f"(lv) : "memory");
            __syncwarp();
            if (lane == 0) mbar_arrive(bars + BAR_P);
            if (tid == 0) PROF(15);
            mbar_wait_cluster(bars + BAR_P, 0);
            const float4* ls = reinterpret_cast<const float4*>(smem + SM_LS);
            const float4 v0 = ls[g * 4 + t], v1 = ls[(g + 8) * 4 + t];
            l0 = (v0.x + v0.y) + (v0.z + v0.w);
            l1 = (v1.x + v1.y) + (v1.z + v1.w);
            l0 += __shfl_xor_sync(0xffffffffu, l0, 1); l1 += __shfl_xor_sync(0xffffffffu, l1, 1);
            l0 += __shfl_xor_sync(0xffffffffu, l0, 2); l1 += __shfl_xor_sync(0xffffffffu, l1, 2);
            inv0 = 1.f / l0; inv1 = 1.f / l1;
        }
        if (tid == 0) PROF(6);

        float oa[4][4];
#pragma unroll
        for (int i = 0; i < 4; i++) { oa[i][0] = oa[i][1] = oa[i][2] = oa[i][3] = 0.f; }
        {
            const uint32_t va = sb + SM_RING + ((mi & 1) * 64 + (mi >> 1) * 8 + r8) * 128 + ((warp ^ r8) << 4);
            const uint4* pf = reinterpret_cast<const uint4*>(smem + SM_A) + lane;
            int s = tile_slot(16);
            uint32_t ph = tile_par(16);
#pragma unroll 1
            for (int v = 0; v < 16; v++) {
                uint4 p[8];
#pragma unroll
                for (int j = 0; j < 8; j++) p[j] = pf[(((v >> 3) * 8 + j) * 8 + (v & 7)) * 32];
                if (v == 15) mbar_wait(bars + BAR_OK, 0);
                mbar_wait(bars + BAR_FULL + 8 * s, ph);
#pragma unroll
                for (int j2 = 0; j2 < 4; j2++) {
                    uint32_t vf[4];
                    ldsm4t(vf, va + s * STAGE_BYTES + j2 * 2048);
                    mma16816(oa[(2 * j2) & 3], p[2 * j2].x, p[2 * j2].y, p[2 * j2].z, p[2 * j2].w, vf[0], vf[1]);
                    mma16816(oa[(2 * j2 + 1) & 3], p[2 * j2 + 1].x, p[2 * j2 + 1].y, p[2 * j2 + 1].z, p[2 * j2 + 1].w, vf[2], vf[3]);
                }
                __syncwarp();
                if (lane == 0) mbar_arrive(bars + BAR_EMPTY + 8 * s);
                if (++s == NSTAGE) { s = 0; ph ^= 1; }
                if (tid == 0) PROF(48 + v);
            }
        }
        if (tid == 0) PROF(7);
        const int ki = hkv * 2 + r;
        {
            const float o0 = ((oa[0][0] + oa[1][0]) + (oa[2][0] + oa[3][0])) * inv0;
            const float o1 = ((oa[0][1] + oa[1][1]) + (oa[2][1] + oa[3][1])) * inv0;
            const float o2 = ((oa[0][2] + oa[1][2]) + (oa[2][2] + oa[3][2])) * inv1;
            const float o3 = ((oa[0][3] + oa[1][3]) + (oa[2][3] + oa[3][3])) * inv1;
            uint2* dst = reinterpret_cast<uint2*>(g_o) +
                         ((((ki * 4 + (b >> 1)) * 8 + warp) * 32 + ((b & 1) * 4 + (g & 3)) * 4 + t) * 2 + (g >> 2));
            st_relaxed_v2(dst, nz(pack_bf16(o0, o1)), nz(pack_bf16(o2, o3)));
        }

        {
            const int mp = warp & 1, nt = warp >> 1;
            const uint4* osrc = &g_o[(ki * 4 + nt) * 256 + lane];
            uint4 of[8];
            const uint32_t wo_s = sb + (mi >> 1) * 4096 + r8 * 128;
            const uint32_t sw0 = ((mp * 4 + (mi & 1)) ^ r8) << 4, sw1 = ((mp * 4 + 2 + (mi & 1)) ^ r8) << 4;
            uint32_t wf[3][8][4];
#pragma unroll
            for (int qd = 0; qd < 3; qd++) {
                if (qd == GQA_FIRSTPOLL) {
#pragma unroll
                    for (int w = 0; w < 8; w++) of[w] = ld_relaxed_v4(osrc + w * 32);
                } else if (qd > GQA_FIRSTPOLL) {
#pragma unroll
                    for (int w = 0; w < 8; w++) if (!valid4(of[w])) of[w] = ld_relaxed_v4(osrc + w * 32);
                }
                mbar_wait(bars + BAR_WO + 8 * qd, 0);
#pragma unroll
                for (int k = 0; k < 4; k++) {
                    const uint32_t a = wo_s + tile_slot(32 + (qd >> 1)) * STAGE_BYTES + (qd & 1) * 8192 + (k & 1) * 2048 + (k >> 1) * 1024;
                    ldsm4t(wf[qd][2 * k], a + sw0);
                    ldsm4t(wf[qd][2 * k + 1], a + sw1);
                }
            }
            if (tid == 0) PROF(8);
            int it = 0;
            while (true) {
                bool ok = true;
#pragma unroll
                for (int w = 0; w < 8; w++) {
                    if (!valid4(of[w])) { of[w] = ld_relaxed_v4(osrc + w * 32); ok = false; }
                }
                if (__all_sync(0xffffffffu, ok)) break;
                if (++it > SPIN_LIMIT) __trap();
            }
            if (tid == 0) PROF(9);
            float acc[2][2][4];
#pragma unroll
            for (int i = 0; i < 4; i++) { acc[0][0][i] = acc[0][1][i] = acc[1][0][i] = acc[1][1][i] = 0.f; }
#pragma unroll
            for (int qd = 0; qd < 3; qd++) {
#pragma unroll
                for (int k = 0; k < 4; k++) {
                    const uint4& o4 = of[qd * 2 + (k >> 1)];
                    const uint32_t b0 = (k & 1) ? o4.z : o4.x, b1 = (k & 1) ? o4.w : o4.y;
                    mma16816(acc[0][k & 1], wf[qd][2 * k][0], wf[qd][2 * k][1], wf[qd][2 * k][2], wf[qd][2 * k][3], b0, b1);
                    mma16816(acc[1][k & 1], wf[qd][2 * k + 1][0], wf[qd][2 * k + 1][1], wf[qd][2 * k + 1][2], wf[qd][2 * k + 1][3], b0, b1);
                }
            }
            mbar_wait(bars + BAR_WO + 8 * 3, 0);
            if (tid == 0) PROF(10);
#pragma unroll
            for (int k = 0; k < 4; k++) {
                const uint32_t a = wo_s + tile_slot(33) * STAGE_BYTES + 8192 + (k & 1) * 2048 + (k >> 1) * 1024;
                uint32_t f0[4], f1[4];
                ldsm4t(f0, a + sw0);
                ldsm4t(f1, a + sw1);
                const uint4& o4 = of[6 + (k >> 1)];
                const uint32_t b0 = (k & 1) ? o4.z : o4.x, b1 = (k & 1) ? o4.w : o4.y;
                mma16816(acc[0][k & 1], f0[0], f0[1], f0[2], f0[3], b0, b1);
                mma16816(acc[1][k & 1], f1[0], f1[1], f1[2], f1[3], b0, b1);
            }
            uint2* pd = reinterpret_cast<uint2*>(g_part) + (((b * 16 + nt * 4 + t) * 8 + mp * 4) * 16 + ki) * 8 + g;
#pragma unroll
            for (int mt = 0; mt < 2; mt++) {
#pragma unroll
                for (int hf = 0; hf < 2; hf++) {
                    st_relaxed_v2(pd + (mt * 2 + hf) * 128,
                                  nz(__float_as_uint(acc[mt][0][2 * hf] + acc[mt][1][2 * hf])),
                                  nz(__float_as_uint(acc[mt][0][2 * hf + 1] + acc[mt][1][2 * hf + 1])));
                }
            }
        }
        if (tid == 0) PROF(11);

        {
            const uint4* src = &g_part[((b * 16 + ki) * 8 + warp) * 64 + lane];
            uint4 u0 = ld_relaxed_v4(src), u1 = ld_relaxed_v4(src + 32);
            int it = 0;
            while (true) {
                bool ok = true;
                if (!valid4(u0)) { u0 = ld_relaxed_v4(src); ok = false; }
                if (!valid4(u1)) { u1 = ld_relaxed_v4(src + 32); ok = false; }
                if (__all_sync(0xffffffffu, ok)) break;
                if (++it > SPIN_LIMIT) __trap();
            }
            if (tid == 0) PROF(12);
            float v0 = __uint_as_float(u0.x) + __uint_as_float(u1.x);
            float v1 = __uint_as_float(u0.y) + __uint_as_float(u1.y);
            float v2 = __uint_as_float(u0.z) + __uint_as_float(u1.z);
            float v3 = __uint_as_float(u0.w) + __uint_as_float(u1.w);
#pragma unroll
            for (int d = 4; d < 32; d <<= 1) {
                v0 += __shfl_xor_sync(0xffffffffu, v0, d);
                v1 += __shfl_xor_sync(0xffffffffu, v1, d);
                v2 += __shfl_xor_sync(0xffffffffu, v2, d);
                v3 += __shfl_xor_sync(0xffffffffu, v3, d);
            }
            if (lane < 8) {
                const uint32_t w = (lane < 4) ? pack_bf16(v0, v2) : pack_bf16(v1, v3);
                reinterpret_cast<uint32_t*>(out)[((2 * ki + (lane >> 2)) * 512 + b * 64 + warp * 8) / 2 + (lane & 3)] = w;
            }
        }
        if (tid == 0) PROF(13);
    }
}

typedef CUresult (*EncodeTiledFn)(CUtensorMap*, CUtensorMapDataType, cuuint32_t, void*, const cuuint64_t*, const cuuint64_t*,
                                  const cuuint32_t*, const cuuint32_t*, CUtensorMapInterleave, CUtensorMapSwizzle,
                                  CUtensorMapL2promotion, CUtensorMapFloatOOBfill);

void encode3d(EncodeTiledFn enc, CUtensorMap* tm, const void* base, cuuint64_t d0, cuuint64_t d1, cuuint64_t d2,
              cuuint64_t s1, cuuint64_t s2, cuuint32_t b0, cuuint32_t b1, cuuint32_t b2,
              CUtensorMapSwizzle sw = CU_TENSOR_MAP_SWIZZLE_128B) {
    const cuuint64_t dims[3] = {d0, d1, d2};
    const cuuint64_t strides[2] = {s1, s2};
    const cuuint32_t box[3] = {b0, b1, b2};
    const cuuint32_t es[3] = {1, 1, 1};
    enc(tm, CU_TENSOR_MAP_DATA_TYPE_BFLOAT16, 3, const_cast<void*>(base), dims, strides, box, es,
        CU_TENSOR_MAP_INTERLEAVE_NONE, sw, CU_TENSOR_MAP_L2_PROMOTION_L2_256B,
        CU_TENSOR_MAP_FLOAT_OOB_FILL_NONE);
}

}

extern "C" void kernel_launch(void* const* d_in, const int* in_sizes, int n_in, void* d_out, int out_size) {
    (void)in_sizes; (void)n_in; (void)out_size;
    const __nv_bfloat16* x = (const __nv_bfloat16*)d_in[0];
    const __nv_bfloat16* kc = (const __nv_bfloat16*)d_in[1];
    const __nv_bfloat16* vc = (const __nv_bfloat16*)d_in[2];
    const __nv_bfloat16* wq = (const __nv_bfloat16*)d_in[3];
    const __nv_bfloat16* wo = (const __nv_bfloat16*)d_in[4];

    static EncodeTiledFn enc = nullptr;
    static Scratch* scr = nullptr;
    if (!enc) {
        cudaGetSymbolAddress((void**)&scr, g_scratch);
        void* fn = nullptr;
        cudaDriverEntryPointQueryResult st;
        cudaGetDriverEntryPoint("cuTensorMapEncodeTiled", &fn, cudaEnableDefault, &st);
        enc = (EncodeTiledFn)fn;
        cudaFuncSetAttribute(gqa_fused_kernel, cudaFuncAttributeMaxDynamicSharedMemorySize, SM_TOTAL + SM_EXTRA);
    }
    CUtensorMap tmK, tmV, tmWo, tmWq, tmX;
    encode3d(enc, &tmWq, wq, 4096, 256, 2, 8192, 256 * 8192, 32, 256, 2, CU_TENSOR_MAP_SWIZZLE_64B);
    encode3d(enc, &tmX, x, 64, 32, 8, 1024, 128, 64, 32, 8);
    encode3d(enc, &tmK, kc, 64, 131072, 2, 256, 128, 64, 64, 2);
    encode3d(enc, &tmV, vc, 64, 131072, 2, 256, 128, 64, 128, 1);
    encode3d(enc, &tmWo, wo, 512, 128, 32, 1024, 131072, 64, 16, 4);
    gqa_fused_kernel<<<128, NTHREADS, SM_TOTAL + SM_EXTRA, cudaStreamPerThread>>>(wq, x, (__nv_bfloat16*)d_out, scr, kc, tmK, tmV, tmWo, tmWq, tmX);
}
```

```cpp
#include <cuda_runtime.h>
#include <cuda.h>
#include <cuda_bf16.h>
#include <stdint.h>
#include <stddef.h>

namespace {

constexpr int NSTAGE = 10;
constexpr int STAGE_BYTES = 16384;
#define GQA_WINDOW 6
#define GQA_W0 2
#define GQA_W1 6
#define GQA_W1_UNTIL 8
#define GQA_PF_K 0
#define GQA_PF_WQ 1
#define GQA_TAU 645
#define GQA_T1 1600
#define GQA_FIRSTPOLL 2
#define GQA_STAGGER 0
#define GQA_EARLY3 1
#define GQA_E4DELAY 400
#define GQA_PHASE 0
#define GQA_GATHER_TILE 31
#define GQA_GDELAY 400
#define GQA_WO_TRIG 27
#define GQA_WO_OFF 0
#define GQA_WO_DT 330
#define GQA_PRE 2
#define GQA_WO_T 22100
#define GQA_E4V2 0
#define GQA_START_TID 0
#define GQA_QDELAY 4000
#define GQA_PF_X 1
#define GQA_WQ_PROMO CU_TENSOR_MAP_L2_PROMOTION_L2_256B
#define GQA_KHINT 1
#define GQA_VHINT 1
constexpr int NTHREADS = 384;

constexpr int SM_RING = 0;
constexpr int SM_A = NSTAGE * STAGE_BYTES;
constexpr int SM_BAR = SM_A + 65536;
constexpr int SM_MX = SM_BAR + 320;
constexpr int SM_LS = SM_MX + 1024;
constexpr int SM_TOTAL = SM_LS + 1024;

constexpr int BAR_FULL = 0;
constexpr int BAR_EMPTY = BAR_FULL + 8 * 13;
constexpr int BAR_WO = BAR_EMPTY + 8 * NSTAGE;
constexpr int BAR_MX = BAR_WO + 32;
constexpr int BAR_P = BAR_MX + 8;
constexpr int BAR_OK = BAR_P + 8;
constexpr int BAR_WQ = BAR_OK + 8;
constexpr int BAR_AFREE = BAR_WQ + 8;
constexpr int BAR_O = BAR_AFREE + 8;
constexpr int BAR_GO = BAR_O + 32;
constexpr int BAR_END = BAR_GO + 8;
static_assert(BAR_END <= 320, "barrier area");

__host__ __device__ constexpr int tile_seq(int n) { return n < 10 ? n : n - 3; }
__host__ __device__ constexpr int tile_slot(int n) { return (n >= 10 && n < 13) ? n : tile_seq(n) % NSTAGE; }
__host__ __device__ constexpr int tile_par(int n) { return (n >= 10 && n < 13) ? 0 : (tile_seq(n) / NSTAGE) & 1; }

constexpr int SPIN_LIMIT = 1 << 22;

struct Scratch {
    uint4 q[64 * 16 * 16];
    uint4 o[16 * 4 * 8 * 32];
    uint4 part[8 * 16 * 8 * 16 * 4];
    unsigned int cnt[32];
};
__device__ Scratch g_scratch;

#define PROF(slot)
constexpr int SM_EXTRA = 0;

__device__ __forceinline__ uint32_t smem_u32(const void* p) { return (uint32_t)__cvta_generic_to_shared(p); }
__device__ __forceinline__ void give_up() {
    asm volatile("st.volatile.global.u32 [%0], %1;\n\texit;" :: "l"(0ull), "r"(0) : "memory");
}
__device__ __forceinline__ void mbar_init(uint32_t bar, uint32_t count) {
    asm volatile("mbarrier.init.shared::cta.b64 [%0], %1;" :: "r"(bar), "r"(count) : "memory");
}
__device__ __forceinline__ void mbar_expect_tx(uint32_t bar, uint32_t bytes) {
    asm volatile("mbarrier.arrive.expect_tx.shared::cta.b64 _, [%0], %1;" :: "r"(bar), "r"(bytes) : "memory");
}
__device__ __forceinline__ void mbar_arrive(uint32_t bar) {
    asm volatile("mbarrier.arrive.shared::cta.b64 _, [%0];" :: "r"(bar) : "memory");
}
__device__ __forceinline__ void mbar_arrive_cluster(uint32_t bar_cluster_addr) {
    asm volatile("mbarrier.arrive.release.cluster.shared::cluster.b64 _, [%0];" :: "r"(bar_cluster_addr) : "memory");
}
__device__ __forceinline__ void mbar_wait(uint32_t bar, uint32_t parity) {
    uint32_t ok;
    int it = 0;
    do {
        asm volatile("{\n.reg .pred p;\nmbarrier.try_wait.parity.shared::cta.b64 p, [%1], %2;\nselp.u32 %0, 1, 0, p;\n}"
                     : "=r"(ok) : "r"(bar), "r"(parity) : "memory");
        if (++it > SPIN_LIMIT) give_up();
    } while (!ok);
}
__device__ __forceinline__ bool mbar_test(uint32_t bar, uint32_t parity) {
    uint32_t ok;
    asm volatile("{\n.reg .pred p;\nmbarrier.test_wait.parity.shared::cta.b64 p, [%1], %2;\nselp.u32 %0, 1, 0, p;\n}"
                 : "=r"(ok) : "r"(bar), "r"(parity) : "memory");
    return __all_sync(0xffffffffu, ok != 0);
}
__device__ __forceinline__ void mbar_wait_cluster(uint32_t bar, uint32_t parity) {
    uint32_t ok;
    int it = 0;
    do {
        asm volatile("{\n.reg .pred p;\nmbarrier.try_wait.parity.acquire.cluster.shared::cta.b64 p, [%1], %2;\nselp.u32 %0, 1, 0, p;\n}"
                     : "=r"(ok) : "r"(bar), "r"(parity) : "memory");
        if (++it > SPIN_LIMIT) give_up();
    } while (!ok);
}
__device__ __forceinline__ void tma3d(uint32_t dst, const CUtensorMap* tm, int c0, int c1, int c2, uint32_t bar) {
    asm volatile("cp.async.bulk.tensor.3d.shared::cluster.global.mbarrier::complete_tx::bytes [%0], [%1, {%3, %4, %5}], [%2];"
                 :: "r"(dst), "l"(tm), "r"(bar), "r"(c0), "r"(c1), "r"(c2) : "memory");
}
__device__ __forceinline__ void tma3d_hint(uint32_t dst, const CUtensorMap* tm, int c0, int c1, int c2, uint32_t bar, uint64_t pol) {
    asm volatile("cp.async.bulk.tensor.3d.shared::cluster.global.mbarrier::complete_tx::bytes.L2::cache_hint [%0], [%1, {%3, %4, %5}], [%2], %6;"
                 :: "r"(dst), "l"(tm), "r"(bar), "r"(c0), "r"(c1), "r"(c2), "l"(pol) : "memory");
}
__device__ __forceinline__ void cp_async16(uint32_t dst, const void* src) {
    asm volatile("cp.async.cg.shared.global [%0], [%1], 16;" :: "r"(dst), "l"(src) : "memory");
}
__device__ __forceinline__ uint4 ldg_nc(const void* p) {
    uint4 v;
    asm volatile("ld.global.nc.L1::no_allocate.v4.u32 {%0, %1, %2, %3}, [%4];" : "=r"(v.x), "=r"(v.y), "=r"(v.z), "=r"(v.w) : "l"(p));
    return v;
}
__device__ __forceinline__ void ldsm4(uint32_t (&r)[4], uint32_t addr) {
    asm volatile("ldmatrix.sync.aligned.m8n8.x4.shared.b16 {%0, %1, %2, %3}, [%4];"
                 : "=r"(r[0]), "=r"(r[1]), "=r"(r[2]), "=r"(r[3]) : "r"(addr) : "memory");
}
__device__ __forceinline__ void ldsm4t(uint32_t (&r)[4], uint32_t addr) {
    asm volatile("ldmatrix.sync.aligned.m8n8.x4.trans.shared.b16 {%0, %1, %2, %3}, [%4];"
                 : "=r"(r[0]), "=r"(r[1]), "=r"(r[2]), "=r"(r[3]) : "r"(addr) : "memory");
}
__device__ __forceinline__ void mma16816(float (&c)[4], uint32_t a0, uint32_t a1, uint32_t a2, uint32_t a3, uint32_t b0, uint32_t b1) {
    asm volatile("mma.sync.aligned.m16n8k16.row.col.f32.bf16.bf16.f32 {%0, %1, %2, %3}, {%4, %5, %6, %7}, {%8, %9}, {%0, %1, %2, %3};"
                 : "+f"(c[0]), "+f"(c[1]), "+f"(c[2]), "+f"(c[3]) : "r"(a0), "r"(a1), "r"(a2), "r"(a3), "r"(b0), "r"(b1));
}
__device__ __forceinline__ uint32_t pack_bf16(float lo, float hi) {
    uint32_t r;
    asm("cvt.rn.bf16x2.f32 %0, %1, %2;" : "=r"(r) : "f"(hi), "f"(lo));
    return r;
}
__device__ __forceinline__ float ex2(float x) {
    float r;
    asm("ex2.approx.ftz.f32 %0, %1;" : "=f"(r) : "f"(x));
    return r;
}
__device__ __forceinline__ uint4 ld_relaxed_v4(const uint4* p) {
    uint4 v;
    asm volatile("ld.relaxed.gpu.global.v4.u32 {%0, %1, %2, %3}, [%4];" : "=r"(v.x), "=r"(v.y), "=r"(v.z), "=r"(v.w) : "l"(p) : "memory");
    return v;
}
__device__ __forceinline__ uint4 lds128(uint32_t a) {
    uint4 v;
    asm volatile("ld.shared.v4.u32 {%0, %1, %2, %3}, [%4];" : "=r"(v.x), "=r"(v.y), "=r"(v.z), "=r"(v.w) : "r"(a) : "memory");
    return v;
}
__device__ __forceinline__ void sts128(uint32_t a, const uint4& v) {
    asm volatile("st.shared.v4.u32 [%0], {%1, %2, %3, %4};" :: "r"(a), "r"(v.x), "r"(v.y), "r"(v.z), "r"(v.w) : "memory");
}
__device__ __forceinline__ void st_relaxed_v2(void* p, uint32_t a, uint32_t b) {
    asm volatile("st.relaxed.gpu.global.v2.u32 [%0], {%1, %2};" :: "l"(p), "r"(a), "r"(b) : "memory");
}
__device__ __forceinline__ uint32_t nz(uint32_t w) { return w == 0u ? 0x80000000u : w; }
__device__ __forceinline__ bool valid4(const uint4& v) { return v.x != 0u && v.y != 0u && v.z != 0u && v.w != 0u; }
__device__ __forceinline__ void bar_compute() { asm volatile("bar.sync 1, 256;" ::: "memory"); }

__device__ __forceinline__ void arrive_and_wait(unsigned int* cnt, unsigned int n) {
    unsigned int old;
    asm volatile("atom.add.release.gpu.global.u32 %0, [%1], 1;" : "=r"(old) : "l"(cnt) : "memory");
    const unsigned int target = (old | (n - 1)) + 1;
    unsigned int cur;
    int it = 0;
    do {
        asm volatile("ld.acquire.gpu.global.u32 %0, [%1];" : "=r"(cur) : "l"(cnt) : "memory");
        if (++it > SPIN_LIMIT) give_up();
    } while ((int)(cur - target) < 0);
}

__global__ void __cluster_dims__(2, 1, 1) __launch_bounds__(NTHREADS, 1)
gqa_fused_kernel(const __nv_bfloat16* __restrict__ wq, const __nv_bfloat16* __restrict__ x, __nv_bfloat16* __restrict__ out,
                 Scratch* __restrict__ scr, const __nv_bfloat16* __restrict__ kc,
                 const __grid_constant__ CUtensorMap tmK, const __grid_constant__ CUtensorMap tmV,
                 const __grid_constant__ CUtensorMap tmWo, const __grid_constant__ CUtensorMap tmWq,
                 const __grid_constant__ CUtensorMap tmX) {
    extern __shared__ __align__(1024) unsigned char smem[];
    const int tid = threadIdx.x;
    uint4* const g_q = scr->q;
    uint4* const g_o = scr->o;
    uint4* const g_part = scr->part;
    unsigned int* const g_cnt = scr->cnt;
    const uint32_t sb = smem_u32(smem);
    const uint32_t bars = sb + SM_BAR;
    const int warp = tid >> 5, lane = tid & 31;
    const int r = blockIdx.x & 1;
    const int pair = blockIdx.x >> 1;
    const int b = pair >> 3, hkv = pair & 7;
    const int krow = blockIdx.x * 1024;
    uint64_t pol;
    asm volatile("createpolicy.fractional.L2::evict_first.b64 %0, 1.0;" : "=l"(pol));
    uint32_t t_start;
    asm volatile("mov.u32 %0, %%globaltimer_lo;" : "=r"(t_start));

    if (tid == GQA_START_TID) {
        PROF(21);
        if (GQA_PF_X) asm volatile("cp.async.bulk.prefetch.L2.global [%0], %1;" :: "l"(x + blockIdx.x * 128), "r"(256) : "memory");
        if (GQA_PF_WQ) asm volatile("cp.async.bulk.prefetch.L2.global [%0], %1;" :: "l"(wq + blockIdx.x * 16384), "r"(32768) : "memory");
        PROF(26);
        mbar_init(bars + BAR_WQ, 1);
#pragma unroll
        for (int n = 0; n < GQA_W0; n++) mbar_init(bars + BAR_FULL + 8 * n, 1);
        asm volatile("fence.proxy.async.shared::cta;" ::: "memory");
        PROF(27);
        mbar_expect_tx(bars + BAR_WQ, 65536);
        tma3d(sb + 8 * STAGE_BYTES, &tmX, 0, 0, 0, bars + BAR_WQ);
        tma3d(sb + SM_A, &tmWq, hkv * 512 + (b * 2 + r) * 32, 0, 0, bars + BAR_WQ);
        PROF(28);
#pragma unroll
        for (int n = 0; n < GQA_W0; n++) {
            mbar_expect_tx(bars + BAR_FULL + 8 * n, STAGE_BYTES);
            if (GQA_KHINT) tma3d_hint(sb + n * STAGE_BYTES, &tmK, 0, krow + n * 64, 0, bars + BAR_FULL + 8 * n, pol);
            else tma3d(sb + n * STAGE_BYTES, &tmK, 0, krow + n * 64, 0, bars + BAR_FULL + 8 * n);
        }
        PROF(25);
#pragma unroll
        for (int off = 8 * GQA_W0; off < BAR_END; off += 8)
            if (off != BAR_WQ) mbar_init(bars + off, off < BAR_EMPTY ? 1 : off < BAR_WO ? 8 : off < BAR_MX ? 1 : off < BAR_OK ? 9 : (off >= BAR_O && off < BAR_GO) ? 2 : 1);
        mbar_expect_tx(bars + BAR_MX, 512);
        mbar_expect_tx(bars + BAR_P, 32768 + 512);
        asm volatile("fence.mbarrier_init.release.cluster;" ::: "memory");
        asm volatile("fence.proxy.async.shared::cta;" ::: "memory");
        PROF(29);
    }
    __syncwarp();
    asm volatile("barrier.cluster.arrive.relaxed.aligned;" ::: "memory");
    __syncthreads();

    const int ki = hkv * 2 + r;
    if (__shfl_sync(0xffffffffu, tid >> 7, 0) == 2) {
      asm volatile("setmaxnreg.dec.sync.aligned.u32 40;");
      if (warp == 8) {
        if (lane == 0) {
            asm volatile("prefetch.tensormap [%0];" :: "l"(&tmV) : "memory");
            asm volatile("prefetch.tensormap [%0];" :: "l"(&tmWo) : "memory");
            uint32_t due = t_start + GQA_T1 + (GQA_PHASE ? ((pair * GQA_PHASE) & 63) * GQA_TAU / 64 : 0);
#pragma unroll 1
            for (int n = GQA_W0; n < 32; n++) {
                {
                    uint32_t now;
                    do { asm volatile("mov.u32 %0, %%globaltimer_lo;" : "=r"(now)); } while ((int)(now - due) < 0);
                    due += GQA_TAU;
                }
                const int W = n < GQA_W1_UNTIL ? GQA_W1 : GQA_WINDOW;
                if (n >= W) mbar_wait(bars + BAR_FULL + 8 * tile_slot(n - W), tile_par(n - W));
                const int s = tile_slot(n);
                if (n == 8) mbar_wait(bars + BAR_AFREE, 0);
                if (n >= 13) mbar_wait(bars + BAR_EMPTY + 8 * s, tile_par(n) ^ 1);
                const uint32_t dst = sb + s * STAGE_BYTES;
                const uint32_t fb = bars + BAR_FULL + 8 * s;
                mbar_expect_tx(fb, STAGE_BYTES);
                if (n < 16) {
                    if (GQA_KHINT) tma3d_hint(dst, &tmK, 0, krow + n * 64, 0, fb, pol);
                    else tma3d(dst, &tmK, 0, krow + n * 64, 0, fb);
                } else {
                    if (GQA_VHINT) tma3d_hint(dst, &tmV, 0, pair * 2048 + (n - 16) * 128, r, fb, pol);
                    else tma3d(dst, &tmV, 0, pair * 2048 + (n - 16) * 128, r, fb);
                }
                PROF(64 + n);
                if (n == 31) mbar_arrive(bars + BAR_GO);
            }
            mbar_wait(bars + BAR_EMPTY + 8 * tile_slot(32), tile_par(32) ^ 1);
            mbar_wait(bars + BAR_EMPTY + 8 * tile_slot(33), tile_par(33) ^ 1);
            mbar_wait(bars + BAR_FULL + 8 * tile_slot(GQA_WO_TRIG), tile_par(GQA_WO_TRIG));
            uint32_t wdue;
            asm volatile("mov.u32 %0, %%globaltimer_lo;" : "=r"(wdue));
            wdue += GQA_WO_OFF;
            if ((int)(wdue - (t_start + GQA_WO_T)) < 0) wdue = t_start + GQA_WO_T;
#pragma unroll
            for (int qd = 0; qd < 4; qd++) {
                uint32_t now;
                do { asm volatile("mov.u32 %0, %%globaltimer_lo;" : "=r"(now)); } while ((int)(now - wdue) < 0);
                wdue += GQA_WO_DT;
                mbar_expect_tx(bars + BAR_WO + 8 * qd, 8192);
                tma3d(sb + tile_slot(32 + (qd >> 1)) * STAGE_BYTES + (qd & 1) * 8192, &tmWo, b * 64, r * 64 + qd * 16, hkv * 4, bars + BAR_WO + 8 * qd);
            }
            PROF(16);
        }
      } else if (warp == 9) {
        if (lane == 0) PROF(19);
        mbar_wait(bars + BAR_AFREE, 0);
        const uint4 z = make_uint4(0u, 0u, 0u, 0u);
#pragma unroll 1
        for (int i = 0; i < 4; i++) g_o[blockIdx.x * 128 + i * 32 + lane] = z;
#pragma unroll 4
        for (int i = 0; i < 16; i++) g_part[blockIdx.x * 512 + i * 32 + lane] = z;
        __syncwarp();
        if (lane == 0) {
            arrive_and_wait(&g_cnt[0], 128);
            mbar_arrive(bars + BAR_OK);
            PROF(20);
        }
      }
        __syncwarp();
        asm volatile("barrier.cluster.wait.acquire.aligned;" ::: "memory");
    } else {
        asm volatile("setmaxnreg.inc.sync.aligned.u32 232;");
        const int g = lane >> 2, t = lane & 3;
        const int mi = lane >> 3, r8 = lane & 7;
        const uint32_t ws = sb + SM_A;
        mbar_wait(bars + BAR_WQ, 0);
        if (tid == 0) PROF(1);

        {
            float acc[4][4];
#pragma unroll
            for (int nt = 0; nt < 4; nt++) { acc[nt][0] = acc[nt][1] = acc[nt][2] = acc[nt][3] = 0.f; }
            const uint32_t wa = ws + ((warp >> 1) * 128 + lane) * 64;
            const uint32_t xa = sb + 8 * STAGE_BYTES + (warp >> 1) * 8192 + ((warp & 1) * 16 + (mi & 1) * 8 + r8) * 128;
#pragma unroll
            for (int i = 0; i < 4; i++) {
                uint32_t a0[4], a1[4];
                ldsm4(a0, xa + (i >> 1) * 4096 + ((((i & 1) * 4 + (mi >> 1)) ^ r8) << 4));
                ldsm4(a1, xa + (i >> 1) * 4096 + ((((i & 1) * 4 + 2 + (mi >> 1)) ^ r8) << 4));
#pragma unroll
                for (int nt = 0; nt < 4; nt++) {
                    uint32_t bw[4];
                    ldsm4t(bw, wa + i * 2048 + ((nt ^ (r8 >> 1)) << 4));
                    mma16816(acc[nt], a0[0], a0[1], a0[2], a0[3], bw[0], bw[1]);
                    mma16816(acc[nt], a1[0], a1[1], a1[2], a1[3], bw[2], bw[3]);
                }
            }
            if (tid == 0) PROF(24);
            float4* red = reinterpret_cast<float4*>(smem + SM_A + 32768);
#pragma unroll
            for (int hf = 0; hf < 2; hf++) {
                const int idx = (warp >> 1) * 256 + ((warp & 1) * 16 + hf * 8 + g) * 4 + t;
                red[idx] = make_float4(acc[0][2 * hf], acc[0][2 * hf + 1], acc[1][2 * hf], acc[1][2 * hf + 1]);
                red[idx + 128] = make_float4(acc[2][2 * hf], acc[2][2 * hf + 1], acc[3][2 * hf], acc[3][2 * hf + 1]);
            }
            bar_compute();
            if (tid < 128) {
                uint32_t w[4];
#pragma unroll
                for (int hf = 0; hf < 2; hf++) {
                    const float4 v0 = red[hf * 128 + tid], v1 = red[256 + hf * 128 + tid], v2 = red[512 + hf * 128 + tid], v3 = red[768 + hf * 128 + tid];
                    w[2 * hf] = nz(pack_bf16((v0.x + v1.x) + (v2.x + v3.x), (v0.y + v1.y) + (v2.y + v3.y)));
                    w[2 * hf + 1] = nz(pack_bf16((v0.z + v1.z) + (v2.z + v3.z), (v0.w + v1.w) + (v2.w + v3.w)));
                }
                uint4* dst = &g_q[(((tid >> 4) * 8 + hkv) * 16 + b * 2 + r) * 16 + (tid & 15)];
                asm volatile("st.relaxed.gpu.global.v4.u32 [%0], {%1, %2, %3, %4};" :: "l"(dst), "r"(w[0]), "r"(w[1]), "r"(w[2]), "r"(w[3]) : "memory");
            }
        }
        if (tid == 0) PROF(2);
        uint4 qf[8];
        {
            const uint4* qsrc = &g_q[pair * 256 + tid];
            bar_compute();
            if (tid == 0) mbar_arrive(bars + BAR_AFREE);
            { long long t0 = clock64(); while (clock64() - t0 < GQA_QDELAY) {} }
            uint4 w = ld_relaxed_v4(qsrc);
            int it = 0;
            while (!valid4(w)) {
                w = ld_relaxed_v4(qsrc);
                if (++it > SPIN_LIMIT) give_up();
            }
            uint4* qs = reinterpret_cast<uint4*>(smem + SM_A + 49152);
            qs[tid] = w;
            bar_compute();
#pragma unroll
            for (int i = 0; i < 8; i++) qf[i] = qs[((g >> 2) * 4 + (i & 1) * 8 + (i >> 1)) * 16 + (g & 3) * 4 + t];
        }
        if (tid == 0) PROF(3);

        float S[16][4];
        {
            const uint32_t ka = sb + SM_RING + (warp * 8 + r8) * 128;
#pragma unroll
            for (int n = 0; n < 16; n++) {
                const int s = tile_slot(n);
                mbar_wait(bars + BAR_FULL + 8 * s, tile_par(n));
                float e[4] = {0.f, 0.f, 0.f, 0.f}, o[4] = {0.f, 0.f, 0.f, 0.f};
#pragma unroll
                for (int i = 0; i < 4; i++) {
                    uint32_t kf[4];
                    ldsm4(kf, ka + s * STAGE_BYTES + (i >> 1) * 8192 + (((((i & 1) << 2) + mi) ^ r8) << 4));
                    mma16816(e, qf[2 * i].x, qf[2 * i + 1].x, qf[2 * i].y, qf[2 * i + 1].y, kf[0], kf[1]);
                    mma16816(o, qf[2 * i].z, qf[2 * i + 1].z, qf[2 * i].w, qf[2 * i + 1].w, kf[2], kf[3]);
                }
#pragma unroll
                for (int i = 0; i < 4; i++) S[n][i] = e[i] + o[i];
                if (s < NSTAGE) {
                    __syncwarp();
                    if (lane == 0) mbar_arrive(bars + BAR_EMPTY + 8 * s);
                }
                if (tid == 0) PROF(32 + n);
            }
        }
        if (tid == 0) PROF(5);

        asm volatile("barrier.cluster.wait.acquire.aligned;" ::: "memory");
        uint32_t peer;
        asm("mapa.shared::cluster.u32 %0, %1, %2;" : "=r"(peer) : "r"(sb), "r"(r ^ 1));
        float inv0, inv1;
        {
            float m0 = fmaxf(S[0][0], S[0][1]), m1 = fmaxf(S[0][2], S[0][3]);
#pragma unroll
            for (int n = 1; n < 16; n++) { m0 = fmaxf(m0, fmaxf(S[n][0], S[n][1])); m1 = fmaxf(m1, fmaxf(S[n][2], S[n][3])); }
            m0 = fmaxf(m0, __shfl_xor_sync(0xffffffffu, m0, 1)); m1 = fmaxf(m1, __shfl_xor_sync(0xffffffffu, m1, 1));
            m0 = fmaxf(m0, __shfl_xor_sync(0xffffffffu, m0, 2)); m1 = fmaxf(m1, __shfl_xor_sync(0xffffffffu, m1, 2));
            const uint32_t off = (uint32_t)(((t & 1) * 8 + g) * 16 + r * 8 + warp) * 4;
            const float mv = (t & 1) ? m1 : m0;
            if (t & 2) asm volatile("st.async.shared::cluster.mbarrier::complete_tx::bytes.f32 [%0], %1, [%2];" :: "r"(peer + SM_MX + off), "f"(mv), "r"(peer + SM_BAR + BAR_MX) : "memory");
            else asm volatile("st.shared.f32 [%0], %1;" :: "r"(sb + SM_MX + off), "f"(mv) : "memory");
            __syncwarp();
            if (lane == 0) mbar_arrive(bars + BAR_MX);
            mbar_wait_cluster(bars + BAR_MX, 0);
            if (tid == 0) PROF(14);
            if (tid < 128) g_q[pair * 256 + r * 128 + tid] = make_uint4(0u, 0u, 0u, 0u);
            const float4* mx = reinterpret_cast<const float4*>(smem + SM_MX);
            const float4 u0 = mx[g * 4 + t], u1 = mx[(g + 8) * 4 + t];
            m0 = fmaxf(fmaxf(u0.x, u0.y), fmaxf(u0.z, u0.w));
            m1 = fmaxf(fmaxf(u1.x, u1.y), fmaxf(u1.z, u1.w));
            m0 = fmaxf(m0, __shfl_xor_sync(0xffffffffu, m0, 1)); m1 = fmaxf(m1, __shfl_xor_sync(0xffffffffu, m1, 1));
            m0 = fmaxf(m0, __shfl_xor_sync(0xffffffffu, m0, 2)); m1 = fmaxf(m1, __shfl_xor_sync(0xffffffffu, m1, 2));
            const float c = 0.08838834764831845f * 1.4426950408889634f;
            float l0 = 0.f, l1 = 0.f;
            const uint32_t poff = SM_A + (r * 8 + warp) * 4096 + lane * 16;
#pragma unroll
            for (int u = 0; u < 8; u++) {
                float p[8];
#pragma unroll
                for (int i = 0; i < 8; i++) p[i] = ex2((S[2 * u + (i >> 2)][i & 3] - ((i & 2) ? m1 : m0)) * c);
                l0 += (p[0] + p[1]) + (p[4] + p[5]);
                l1 += (p[2] + p[3]) + (p[6] + p[7]);
                const uint32_t a0 = pack_bf16(p[0], p[1]), a1 = pack_bf16(p[2], p[3]), a2 = pack_bf16(p[4], p[5]), a3 = pack_bf16(p[6], p[7]);
                asm volatile("st.shared.v4.u32 [%0], {%1, %2, %3, %4};" :: "r"(sb + poff + u * 512), "r"(a0), "r"(a1), "r"(a2), "r"(a3) : "memory");
            }
            asm volatile("fence.proxy.async.shared::cta;" ::: "memory");
            __syncwarp();
            if (lane == 0)
                asm volatile("cp.async.bulk.shared::cluster.shared::cta.mbarrier::complete_tx::bytes [%0], [%1], %2, [%3];"
                             :: "r"(peer + poff), "r"(sb + poff), "r"(4096), "r"(peer + SM_BAR + BAR_P) : "memory");
            l0 += __shfl_xor_sync(0xffffffffu, l0, 1); l1 += __shfl_xor_sync(0xffffffffu, l1, 1);
            l0 += __shfl_xor_sync(0xffffffffu, l0, 2); l1 += __shfl_xor_sync(0xffffffffu, l1, 2);
            const float lv = (t & 1) ? l1 : l0;
            if (t & 2) asm volatile("st.async.shared::cluster.mbarrier::complete_tx::bytes.f32 [%0], %1, [%2];" :: "r"(peer + SM_LS + off), "f"(lv), "r"(peer + SM_BAR + BAR_P) : "memory");
            else asm volatile("st.shared.f32 [%0], %1;" :: "r"(sb + SM_LS + off), "f"(lv) : "memory");
            __syncwarp();
            if (lane == 0) mbar_arrive(bars + BAR_P);
            if (tid == 0) PROF(15);
            mbar_wait_cluster(bars + BAR_P, 0);
            const float4* ls = reinterpret_cast<const float4*>(smem + SM_LS);
            const float4 v0 = ls[g * 4 + t], v1 = ls[(g + 8) * 4 + t];
            l0 = (v0.x + v0.y) + (v0.z + v0.w);
            l1 = (v1.x + v1.y) + (v1.z + v1.w);
            l0 += __shfl_xor_sync(0xffffffffu, l0, 1); l1 += __shfl_xor_sync(0xffffffffu, l1, 1);
            l0 += __shfl_xor_sync(0xffffffffu, l0, 2); l1 += __shfl_xor_sync(0xffffffffu, l1, 2);
            inv0 = 1.f / l0; inv1 = 1.f / l1;
        }
        if (tid == 0) PROF(6);

        const int mp = warp & 1, nt = warp >> 1;
        const int po = nt * 256 + (lane >> 4) * 32 + mp * 16 + (lane & 15);
        uint32_t o_dst_off = offsetof(Scratch, o) + 8 * ((((ki * 4 + (b >> 1)) * 8 + warp) * 32 + ((b & 1) * 4 + (g & 3)) * 4 + t) * 2 + (g >> 2));
        uint32_t o_src_off = offsetof(Scratch, o) + 16 * (ki * 1024 + po);
        uint32_t p_dst_off = offsetof(Scratch, part) + 16 * ((((b * 16 + nt * 4 + t) * 4 + mp * 2) * 16 + ki) * 8 + g);
        unsigned char* const sc = reinterpret_cast<unsigned char*>(scr);
        uint32_t os_st = sb + tile_slot(24) * STAGE_BYTES + po * 16;
        uint32_t os_ld = sb + tile_slot(24) * STAGE_BYTES + (nt * 256 + lane) * 16;
        uint32_t wa0 = sb + (mi >> 1) * 4096 + r8 * 128 + (((mp * 4 + (mi & 1)) ^ r8) << 4);
        uint32_t wa1 = sb + (mi >> 1) * 4096 + r8 * 128 + (((mp * 4 + 2 + (mi & 1)) ^ r8) << 4);
        uint32_t va = sb + SM_RING + ((mi & 1) * 64 + (mi >> 1) * 8 + r8) * 128 + ((warp ^ r8) << 4);
        uint32_t pa = sb + SM_A + lane * 16;
        uint32_t tb = bars;
        asm volatile("" : "+r"(o_dst_off), "+r"(o_src_off), "+r"(p_dst_off));
        asm volatile("" : "+r"(os_st), "+r"(os_ld), "+r"(wa0), "+r"(wa1), "+r"(va), "+r"(pa), "+r"(tb));

        float oa[4][4];
#pragma unroll
        for (int i = 0; i < 4; i++) { oa[i][0] = oa[i][1] = oa[i][2] = oa[i][3] = 0.f; }
        uint32_t wf[4][8][4];
        auto load_wo = [&](int qd) {
#pragma unroll
            for (int k = 0; k < 4; k++) {
                const uint32_t a = tile_slot(32 + (qd >> 1)) * STAGE_BYTES + (qd & 1) * 8192 + (k & 1) * 2048 + (k >> 1) * 1024;
                ldsm4t(wf[qd][2 * k], wa0 + a);
                ldsm4t(wf[qd][2 * k + 1], wa1 + a);
            }
        };
        auto pv_tile = [&](int v, int s, uint32_t ph) {
            uint4 p[8];
#pragma unroll
            for (int j = 0; j < 8; j++) p[j] = lds128(pa + ((v >> 3) * 64 + (v & 7)) * 512 + j * 4096);
            const uint32_t vs = va + s * STAGE_BYTES;
            mbar_wait(tb + BAR_FULL + 8 * s, ph);
#pragma unroll
            for (int j2 = 0; j2 < 4; j2++) {
                uint32_t vf[4];
                ldsm4t(vf, vs + j2 * 2048);
                mma16816(oa[(2 * j2) & 3], p[2 * j2].x, p[2 * j2].y, p[2 * j2].z, p[2 * j2].w, vf[0], vf[1]);
                mma16816(oa[(2 * j2 + 1) & 3], p[2 * j2 + 1].x, p[2 * j2 + 1].y, p[2 * j2 + 1].z, p[2 * j2 + 1].w, vf[2], vf[3]);
            }
        };
        {
            int s = tile_slot(16);
            uint32_t ph = tile_par(16);
#pragma unroll 1
            for (int v = 0; v < 15; v++) {
                pv_tile(v, s, ph);
                __syncwarp();
                if (lane == 0) mbar_arrive(tb + BAR_EMPTY + 8 * s);
                if (++s == NSTAGE) { s = 0; ph ^= 1; }
                if (tid == 0) PROF(48 + v);
            }
        }
        mbar_wait(tb + BAR_OK, 0);
        mbar_wait(tb + BAR_EMPTY + 8 * tile_slot(24), tile_par(24));
        pv_tile(15, tile_slot(31), tile_par(31));
        {
            const float o0 = ((oa[0][0] + oa[1][0]) + (oa[2][0] + oa[3][0])) * inv0;
            const float o1 = ((oa[0][1] + oa[1][1]) + (oa[2][1] + oa[3][1])) * inv0;
            const float o2 = ((oa[0][2] + oa[1][2]) + (oa[2][2] + oa[3][2])) * inv1;
            const float o3 = ((oa[0][3] + oa[1][3]) + (oa[2][3] + oa[3][3])) * inv1;
            st_relaxed_v2(sc + o_dst_off, nz(pack_bf16(o0, o1)), nz(pack_bf16(o2, o3)));
        }
        if (tid == 0) PROF(7);

        {
            { long long t0 = clock64(); while (clock64() - t0 < GQA_GDELAY) {} }
            const uint4* o_src = reinterpret_cast<const uint4*>(sc + o_src_off);
            uint4 og[4];
#pragma unroll
            for (int j = 0; j < 4; j++) og[j] = ld_relaxed_v4(o_src + j * 64);
            const uint32_t ob = tb + BAR_O + 8 * nt;
            bool done = false;
            int it = 0;
            int rounds = 0;
            auto poll = [&]() {
                bool ok = true;
#pragma unroll
                for (int j = 0; j < 4; j++) {
                    if (!valid4(og[j])) { og[j] = ld_relaxed_v4(o_src + j * 64); ok = false; }
                }
                if (__all_sync(0xffffffffu, ok)) {
#pragma unroll
                    for (int j = 0; j < 4; j++) sts128(os_st + j * 1024, og[j]);
                    __syncwarp();
                    if (lane == 0) mbar_arrive(ob);
                    done = true;
                    if (tid == 0) PROF(8);
                }
            };
            bool have[4];
#pragma unroll
            for (int qd = 0; qd < 4; qd++) {
                while (true) {
                    have[qd] = mbar_test(tb + BAR_WO + 8 * qd, 0);
                    if (have[qd]) break;
                    if (!done) poll();
                    else if (mbar_test(ob, 0)) break;
                    if (++it > SPIN_LIMIT) give_up();
                }
                if (have[qd]) load_wo(qd);
            }
            while (!done) {
                poll();
                if (++it > SPIN_LIMIT) give_up();
            }
            mbar_wait(ob, 0);
            if (tid == 0) PROF(9);
            uint4 of[8];
#pragma unroll
            for (int w = 0; w < 8; w++) of[w] = lds128(os_ld + w * 512);
            float acc[2][4][4];
#pragma unroll
            for (int i = 0; i < 16; i++) { acc[0][i >> 2][i & 3] = acc[1][i >> 2][i & 3] = 0.f; }
#pragma unroll
            for (int qd = 0; qd < 4; qd++) {
                if (!have[qd]) {
                    mbar_wait(tb + BAR_WO + 8 * qd, 0);
                    load_wo(qd);
                }
#pragma unroll
                for (int k = 0; k < 4; k++) {
                    const uint4& o4 = of[qd * 2 + (k >> 1)];
                    const uint32_t b0 = (k & 1) ? o4.z : o4.x, b1 = (k & 1) ? o4.w : o4.y;
                    mma16816(acc[0][k], wf[qd][2 * k][0], wf[qd][2 * k][1], wf[qd][2 * k][2], wf[qd][2 * k][3], b0, b1);
                    mma16816(acc[1][k], wf[qd][2 * k + 1][0], wf[qd][2 * k + 1][1], wf[qd][2 * k + 1][2], wf[qd][2 * k + 1][3], b0, b1);
                }
            }
#pragma unroll
            for (int mt = 0; mt < 2; mt++) {
                uint32_t w[4];
#pragma unroll
                for (int i = 0; i < 4; i++) w[i] = nz(__float_as_uint((acc[mt][0][i] + acc[mt][1][i]) + (acc[mt][2][i] + acc[mt][3][i])));
                asm volatile("st.relaxed.gpu.global.v4.u32 [%0], {%1, %2, %3, %4};" :: "l"(sc + p_dst_off + mt * 2048), "r"(w[0]), "r"(w[1]), "r"(w[2]), "r"(w[3]) : "memory");
            }
        }
        if (tid == 0) PROF(11);

        {
            constexpr int P2 = 64;
            const long long t0 = clock64();
            const uint4* p_src = &g_part[(((b * 16 + ki) * 4 + nt) * 16 + g) * 8 + mp * 4 + t];
            __nv_bfloat16* out_dst = out + (2 * ki + (g & 1)) * 512 + b * 64 + nt * 16 + mp * 4 + t + (g & 2) * 4;
            asm volatile("" : "+l"(p_src), "+l"(out_dst));
            while (clock64() - t0 < GQA_E4DELAY) {}
            uint4 u0 = ld_relaxed_v4(p_src), u1 = ld_relaxed_v4(p_src + P2);
            int it = 0;
            while (true) {
                bool ok = true;
                if (!valid4(u0)) { u0 = ld_relaxed_v4(p_src); ok = false; }
                if (!valid4(u1)) { u1 = ld_relaxed_v4(p_src + P2); ok = false; }
                if (__all_sync(0xffffffffu, ok)) break;
                if (++it > SPIN_LIMIT) give_up();
            }
            if (tid == 0) PROF(12);
            float v0 = __uint_as_float(u0.x) + __uint_as_float(u1.x);
            float v1 = __uint_as_float(u0.y) + __uint_as_float(u1.y);
            float v2 = __uint_as_float(u0.z) + __uint_as_float(u1.z);
            float v3 = __uint_as_float(u0.w) + __uint_as_float(u1.w);
#pragma unroll
            for (int d = 4; d < 32; d <<= 1) {
                v0 += __shfl_xor_sync(0xffffffffu, v0, d);
                v1 += __shfl_xor_sync(0xffffffffu, v1, d);
                v2 += __shfl_xor_sync(0xffffffffu, v2, d);
                v3 += __shfl_xor_sync(0xffffffffu, v3, d);
            }
            if (lane < 16) *out_dst = __float2bfloat16_rn((g & 2) ? ((g & 1) ? v3 : v2) : ((g & 1) ? v1 : v0));
        }
        if (tid == 0) PROF(13);
    }
}

typedef CUresult (*EncodeTiledFn)(CUtensorMap*, CUtensorMapDataType, cuuint32_t, void*, const cuuint64_t*, const cuuint64_t*,
                                  const cuuint32_t*, const cuuint32_t*, CUtensorMapInterleave, CUtensorMapSwizzle,
                                  CUtensorMapL2promotion, CUtensorMapFloatOOBfill);

void encode3d(EncodeTiledFn enc, CUtensorMap* tm, const void* base, cuuint64_t d0, cuuint64_t d1, cuuint64_t d2,
              cuuint64_t s1, cuuint64_t s2, cuuint32_t b0, cuuint32_t b1, cuuint32_t b2,
              CUtensorMapSwizzle sw = CU_TENSOR_MAP_SWIZZLE_128B) {
    const cuuint64_t dims[3] = {d0, d1, d2};
    const cuuint64_t strides[2] = {s1, s2};
    const cuuint32_t box[3] = {b0, b1, b2};
    const cuuint32_t es[3] = {1, 1, 1};
    enc(tm, CU_TENSOR_MAP_DATA_TYPE_BFLOAT16, 3, const_cast<void*>(base), dims, strides, box, es,
        CU_TENSOR_MAP_INTERLEAVE_NONE, sw, CU_TENSOR_MAP_L2_PROMOTION_L2_256B,
        CU_TENSOR_MAP_FLOAT_OOB_FILL_NONE);
}

}

extern "C" void kernel_launch(void* const* d_in, const int* in_sizes, int n_in, void* d_out, int out_size) {
    (void)in_sizes; (void)n_in; (void)out_size;
    const __nv_bfloat16* x = (const __nv_bfloat16*)d_in[0];
    const __nv_bfloat16* kc = (const __nv_bfloat16*)d_in[1];
    const __nv_bfloat16* vc = (const __nv_bfloat16*)d_in[2];
    const __nv_bfloat16* wq = (const __nv_bfloat16*)d_in[3];
    const __nv_bfloat16* wo = (const __nv_bfloat16*)d_in[4];

    static EncodeTiledFn enc = nullptr;
    static Scratch* scr = nullptr;
    if (!enc) {
        cudaGetSymbolAddress((void**)&scr, g_scratch);
        void* fn = nullptr;
        cudaDriverEntryPointQueryResult st;
        cudaGetDriverEntryPoint("cuTensorMapEncodeTiled", &fn, cudaEnableDefault, &st);
        enc = (EncodeTiledFn)fn;
        cudaFuncSetAttribute(gqa_fused_kernel, cudaFuncAttributeMaxDynamicSharedMemorySize, SM_TOTAL + SM_EXTRA);
    }
    CUtensorMap tmK, tmV, tmWo, tmWq, tmX;
    encode3d(enc, &tmWq, wq, 4096, 256, 2, 8192, 256 * 8192, 32, 256, 2, CU_TENSOR_MAP_SWIZZLE_64B);
    encode3d(enc, &tmX, x, 64, 32, 8, 1024, 128, 64, 32, 8);
    encode3d(enc, &tmK, kc, 64, 131072, 2, 256, 128, 64, 64, 2);
    encode3d(enc, &tmV, vc, 64, 131072, 2, 256, 128, 64, 128, 1);
    encode3d(enc, &tmWo, wo, 512, 128, 32, 1024, 131072, 64, 16, 4);
    gqa_fused_kernel<<<128, NTHREADS, SM_TOTAL + SM_EXTRA, cudaStreamPerThread>>>(wq, x, (__nv_bfloat16*)d_out, scr, kc, tmK, tmV, tmWo, tmWq, tmX);
}
```

```cpp
#include <cuda_runtime.h>
#include <cuda.h>
#include <cuda_bf16.h>
#include <stdint.h>
#include <stddef.h>

namespace {

constexpr int NSTAGE = 10;
constexpr int STAGE_BYTES = 16384;
constexpr int NTHREADS = 384;

constexpr int W0 = 2;
constexpr uint32_t T_FIRST = 1600;
constexpr uint32_t T_TILE = 645;
constexpr int WINDOW = 6;
constexpr uint32_t T_WO = 21900;
constexpr uint32_t T_WO_PIECE = 170;
constexpr int Q_DELAY = 4000;
constexpr int O_DELAY = 250;
constexpr int PART_DELAY = 400;

constexpr int SM_A = NSTAGE * STAGE_BYTES;
constexpr int SM_BAR = SM_A + 65536;
constexpr int SM_MX = SM_BAR + 320;
constexpr int SM_LS = SM_MX + 1024;
constexpr int SM_TOTAL = SM_LS + 1024;

constexpr int BAR_FULL = 0;
constexpr int BAR_EMPTY = BAR_FULL + 8 * 13;
constexpr int BAR_WO = BAR_EMPTY + 8 * NSTAGE;
constexpr int BAR_MX = BAR_WO + 32;
constexpr int BAR_P = BAR_MX + 8;
constexpr int BAR_OK = BAR_P + 8;
constexpr int BAR_WQ = BAR_OK + 8;
constexpr int BAR_AFREE = BAR_WQ + 8;
constexpr int BAR_O = BAR_AFREE + 8;
constexpr int BAR_END = BAR_O + 32;
static_assert(BAR_END <= 320, "barrier area");

__host__ __device__ constexpr int tile_seq(int n) { return n < 10 ? n : n - 3; }
__host__ __device__ constexpr int tile_slot(int n) { return (n >= 10 && n < 13) ? n : tile_seq(n) % NSTAGE; }
__host__ __device__ constexpr int tile_par(int n) { return (n >= 10 && n < 13) ? 0 : (tile_seq(n) / NSTAGE) & 1; }
constexpr int X_SLOT = 8;
constexpr int O_TILE = 24;

constexpr int SPIN_LIMIT = 1 << 20;

struct Scratch {
    uint4 q[64 * 16 * 16];
    uint4 o[16 * 4 * 8 * 32];
    uint4 part[8 * 16 * 4 * 16 * 8];
    unsigned int cnt[32];
};
__device__ Scratch g_scratch;

__device__ __forceinline__ uint32_t smem_u32(const void* p) { return (uint32_t)__cvta_generic_to_shared(p); }
__device__ __forceinline__ void give_up() {
    asm volatile("st.volatile.global.u32 [%0], %1;\n\texit;" :: "l"(0ull), "r"(0) : "memory");
}
__device__ __forceinline__ uint32_t now_ns() {
    uint32_t t;
    asm volatile("mov.u32 %0, %%globaltimer_lo;" : "=r"(t));
    return t;
}
__device__ __forceinline__ void wait_until(uint32_t due) {
    for (int i = 0; i < (1 << 16) && (int)(now_ns() - due) < 0; i++) {}
}
__device__ __forceinline__ void spin_clocks(long long t0, int n) { while (clock64() - t0 < n) {} }
__device__ __forceinline__ void mbar_init(uint32_t bar, uint32_t count) {
    asm volatile("mbarrier.init.shared::cta.b64 [%0], %1;" :: "r"(bar), "r"(count) : "memory");
}
__device__ __forceinline__ void mbar_expect_tx(uint32_t bar, uint32_t bytes) {
    asm volatile("mbarrier.arrive.expect_tx.shared::cta.b64 _, [%0], %1;" :: "r"(bar), "r"(bytes) : "memory");
}
__device__ __forceinline__ void mbar_arrive(uint32_t bar) {
    asm volatile("mbarrier.arrive.shared::cta.b64 _, [%0];" :: "r"(bar) : "memory");
}
__device__ __forceinline__ void mbar_wait(uint32_t bar, uint32_t parity) {
    uint32_t ok;
    int it = 0;
    do {
        asm volatile("{\n.reg .pred p;\nmbarrier.try_wait.parity.shared::cta.b64 p, [%1], %2;\nselp.u32 %0, 1, 0, p;\n}"
                     : "=r"(ok) : "r"(bar), "r"(parity) : "memory");
        if (++it > SPIN_LIMIT) give_up();
    } while (!ok);
}
__device__ __forceinline__ bool mbar_test(uint32_t bar, uint32_t parity) {
    uint32_t ok;
    asm volatile("{\n.reg .pred p;\nmbarrier.test_wait.parity.shared::cta.b64 p, [%1], %2;\nselp.u32 %0, 1, 0, p;\n}"
                 : "=r"(ok) : "r"(bar), "r"(parity) : "memory");
    return __all_sync(0xffffffffu, ok != 0);
}
__device__ __forceinline__ void mbar_wait_cluster(uint32_t bar, uint32_t parity) {
    uint32_t ok;
    int it = 0;
    do {
        asm volatile("{\n.reg .pred p;\nmbarrier.try_wait.parity.acquire.cluster.shared::cta.b64 p, [%1], %2;\nselp.u32 %0, 1, 0, p;\n}"
                     : "=r"(ok) : "r"(bar), "r"(parity) : "memory");
        if (++it > SPIN_LIMIT) give_up();
    } while (!ok);
}
__device__ __forceinline__ void tma3d(uint32_t dst, const CUtensorMap* tm, int c0, int c1, int c2, uint32_t bar) {
    asm volatile("cp.async.bulk.tensor.3d.shared::cluster.global.mbarrier::complete_tx::bytes [%0], [%1, {%3, %4, %5}], [%2];"
                 :: "r"(dst), "l"(tm), "r"(bar), "r"(c0), "r"(c1), "r"(c2) : "memory");
}
__device__ __forceinline__ void tma3d_hint(uint32_t dst, const CUtensorMap* tm, int c0, int c1, int c2, uint32_t bar, uint64_t pol) {
    asm volatile("cp.async.bulk.tensor.3d.shared::cluster.global.mbarrier::complete_tx::bytes.L2::cache_hint [%0], [%1, {%3, %4, %5}], [%2], %6;"
                 :: "r"(dst), "l"(tm), "r"(bar), "r"(c0), "r"(c1), "r"(c2), "l"(pol) : "memory");
}
__device__ __forceinline__ void ldsm4(uint32_t (&r)[4], uint32_t addr) {
    asm volatile("ldmatrix.sync.aligned.m8n8.x4.shared.b16 {%0, %1, %2, %3}, [%4];"
                 : "=r"(r[0]), "=r"(r[1]), "=r"(r[2]), "=r"(r[3]) : "r"(addr) : "memory");
}
__device__ __forceinline__ void ldsm4t(uint32_t (&r)[4], uint32_t addr) {
    asm volatile("ldmatrix.sync.aligned.m8n8.x4.trans.shared.b16 {%0, %1, %2, %3}, [%4];"
                 : "=r"(r[0]), "=r"(r[1]), "=r"(r[2]), "=r"(r[3]) : "r"(addr) : "memory");
}
__device__ __forceinline__ void mma16816(float (&c)[4], uint32_t a0, uint32_t a1, uint32_t a2, uint32_t a3, uint32_t b0, uint32_t b1) {
    asm volatile("mma.sync.aligned.m16n8k16.row.col.f32.bf16.bf16.f32 {%0, %1, %2, %3}, {%4, %5, %6, %7}, {%8, %9}, {%0, %1, %2, %3};"
                 : "+f"(c[0]), "+f"(c[1]), "+f"(c[2]), "+f"(c[3]) : "r"(a0), "r"(a1), "r"(a2), "r"(a3), "r"(b0), "r"(b1));
}
__device__ __forceinline__ uint32_t pack_bf16(float lo, float hi) {
    uint32_t r;
    asm("cvt.rn.bf16x2.f32 %0, %1, %2;" : "=r"(r) : "f"(hi), "f"(lo));
    return r;
}
__device__ __forceinline__ float ex2(float x) {
    float r;
    asm("ex2.approx.ftz.f32 %0, %1;" : "=f"(r) : "f"(x));
    return r;
}
__device__ __forceinline__ uint4 ld_relaxed_v4(const uint4* p) {
    uint4 v;
    asm volatile("ld.relaxed.gpu.global.v4.u32 {%0, %1, %2, %3}, [%4];" : "=r"(v.x), "=r"(v.y), "=r"(v.z), "=r"(v.w) : "l"(p) : "memory");
    return v;
}
__device__ __forceinline__ void st_relaxed_v4(void* p, const uint32_t (&w)[4]) {
    asm volatile("st.relaxed.gpu.global.v4.u32 [%0], {%1, %2, %3, %4};" :: "l"(p), "r"(w[0]), "r"(w[1]), "r"(w[2]), "r"(w[3]) : "memory");
}
__device__ __forceinline__ uint4 lds128(uint32_t a) {
    uint4 v;
    asm volatile("ld.shared.v4.u32 {%0, %1, %2, %3}, [%4];" : "=r"(v.x), "=r"(v.y), "=r"(v.z), "=r"(v.w) : "r"(a) : "memory");
    return v;
}
__device__ __forceinline__ void sts128(uint32_t a, const uint4& v) {
    asm volatile("st.shared.v4.u32 [%0], {%1, %2, %3, %4};" :: "r"(a), "r"(v.x), "r"(v.y), "r"(v.z), "r"(v.w) : "memory");
}
__device__ __forceinline__ uint32_t nz(uint32_t w) { return w == 0u ? 0x80000000u : w; }
__device__ __forceinline__ bool valid4(const uint4& v) { return v.x != 0u && v.y != 0u && v.z != 0u && v.w != 0u; }
__device__ __forceinline__ void bar_compute() { asm volatile("bar.sync 1, 256;" ::: "memory"); }

__device__ __forceinline__ void arrive_and_wait(unsigned int* cnt, unsigned int n) {
    unsigned int old;
    asm volatile("atom.add.release.gpu.global.u32 %0, [%1], 1;" : "=r"(old) : "l"(cnt) : "memory");
    const unsigned int target = (old | (n - 1)) + 1;
    unsigned int cur;
    int it = 0;
    do {
        asm volatile("ld.acquire.gpu.global.u32 %0, [%1];" : "=r"(cur) : "l"(cnt) : "memory");
        if (++it > SPIN_LIMIT) give_up();
    } while ((int)(cur - target) < 0);
}

__global__ void __cluster_dims__(2, 1, 1) __launch_bounds__(NTHREADS, 1)
gqa_fused_kernel(const __nv_bfloat16* __restrict__ wq, const __nv_bfloat16* __restrict__ x, __nv_bfloat16* __restrict__ out,
                 Scratch* __restrict__ scr,
                 const __grid_constant__ CUtensorMap tmK, const __grid_constant__ CUtensorMap tmV,
                 const __grid_constant__ CUtensorMap tmWo, const __grid_constant__ CUtensorMap tmWq,
                 const __grid_constant__ CUtensorMap tmX) {
    extern __shared__ __align__(1024) unsigned char smem[];
    const int tid = threadIdx.x;
    uint4* const g_q = scr->q;
    uint4* const g_o = scr->o;
    uint4* const g_part = scr->part;
    const uint32_t sb = smem_u32(smem);
    const uint32_t bars = sb + SM_BAR;
    const int warp = tid >> 5, lane = tid & 31;
    const int r = blockIdx.x & 1;
    const int pair = blockIdx.x >> 1;
    const int b = pair >> 3, hkv = pair & 7;
    const int krow = blockIdx.x * 1024;
    uint64_t pol;
    asm volatile("createpolicy.fractional.L2::evict_first.b64 %0, 1.0;" : "=l"(pol));
    const uint32_t t_start = now_ns();

    if (tid == 0) {
        asm volatile("cp.async.bulk.prefetch.L2.global [%0], %1;" :: "l"(x + blockIdx.x * 128), "r"(256) : "memory");
        asm volatile("cp.async.bulk.prefetch.L2.global [%0], %1;" :: "l"(wq + blockIdx.x * 16384), "r"(32768) : "memory");
        mbar_init(bars + BAR_WQ, 1);
#pragma unroll
        for (int n = 0; n < W0; n++) mbar_init(bars + BAR_FULL + 8 * n, 1);
        asm volatile("fence.proxy.async.shared::cta;" ::: "memory");
        mbar_expect_tx(bars + BAR_WQ, 65536);
        tma3d(sb + X_SLOT * STAGE_BYTES, &tmX, 0, 0, 0, bars + BAR_WQ);
        tma3d(sb + SM_A, &tmWq, hkv * 512 + (b * 2 + r) * 32, 0, 0, bars + BAR_WQ);
#pragma unroll
        for (int n = 0; n < W0; n++) {
            mbar_expect_tx(bars + BAR_FULL + 8 * n, STAGE_BYTES);
            tma3d_hint(sb + n * STAGE_BYTES, &tmK, 0, krow + n * 64, 0, bars + BAR_FULL + 8 * n, pol);
        }
#pragma unroll
        for (int off = 8 * W0; off < BAR_END; off += 8)
            if (off != BAR_WQ)
                mbar_init(bars + off, off < BAR_EMPTY ? 1 : off < BAR_WO ? 8 : off < BAR_MX ? 1 : off < BAR_OK ? 9 : off >= BAR_O ? 2 : 1);
        mbar_expect_tx(bars + BAR_MX, 512);
        mbar_expect_tx(bars + BAR_P, 32768 + 512);
        asm volatile("fence.mbarrier_init.release.cluster;" ::: "memory");
        asm volatile("fence.proxy.async.shared::cta;" ::: "memory");
    }
    __syncwarp();
    asm volatile("barrier.cluster.arrive.relaxed.aligned;" ::: "memory");
    __syncthreads();

    const int ki = hkv * 2 + r;
    if (__shfl_sync(0xffffffffu, tid >> 7, 0) == 2) {
        asm volatile("setmaxnreg.dec.sync.aligned.u32 40;");
        if (warp == 8) {
            if (lane == 0) {
                asm volatile("prefetch.tensormap [%0];" :: "l"(&tmV) : "memory");
                asm volatile("prefetch.tensormap [%0];" :: "l"(&tmWo) : "memory");
                uint32_t due = t_start + T_FIRST;
#pragma unroll 1
                for (int n = W0; n < 32; n++) {
                    wait_until(due);
                    due += T_TILE;
                    if (n >= WINDOW) mbar_wait(bars + BAR_FULL + 8 * tile_slot(n - WINDOW), tile_par(n - WINDOW));
                    const int s = tile_slot(n);
                    if (n == X_SLOT) mbar_wait(bars + BAR_AFREE, 0);
                    if (n >= 13) mbar_wait(bars + BAR_EMPTY + 8 * s, tile_par(n) ^ 1);
                    const uint32_t dst = sb + s * STAGE_BYTES;
                    const uint32_t fb = bars + BAR_FULL + 8 * s;
                    mbar_expect_tx(fb, STAGE_BYTES);
                    if (n < 16) tma3d_hint(dst, &tmK, 0, krow + n * 64, 0, fb, pol);
                    else tma3d_hint(dst, &tmV, 0, pair * 2048 + (n - 16) * 128, r, fb, pol);
                }
                mbar_wait(bars + BAR_EMPTY + 8 * tile_slot(32), tile_par(32) ^ 1);
                mbar_wait(bars + BAR_EMPTY + 8 * tile_slot(33), tile_par(33) ^ 1);
                mbar_wait(bars + BAR_FULL + 8 * tile_slot(27), tile_par(27));
                due = now_ns();
                if ((int)(due - (t_start + T_WO)) < 0) due = t_start + T_WO;
                due += ((blockIdx.x * 37) & 127) * T_WO_PIECE / 128;
#pragma unroll
                for (int u = 0; u < 8; u++) {
                    const int qd = u >> 1, hh = (u & 1) * 2;
                    wait_until(due);
                    due += T_WO_PIECE;
                    if (hh == 0) mbar_expect_tx(bars + BAR_WO + 8 * qd, 8192);
                    tma3d(sb + tile_slot(32 + (qd >> 1)) * STAGE_BYTES + (qd & 1) * 8192 + hh * 2048, &tmWo,
                          b * 64, r * 64 + qd * 16, hkv * 4 + hh, bars + BAR_WO + 8 * qd);
                }
            }
        } else if (warp == 9) {
            mbar_wait(bars + BAR_AFREE, 0);
            const uint4 z = make_uint4(0u, 0u, 0u, 0u);
#pragma unroll 1
            for (int i = 0; i < 4; i++) g_o[(ki * 4 + (b >> 1)) * 256 + (i * 2 + (lane >> 4)) * 32 + (b & 1) * 16 + (lane & 15)] = z;
#pragma unroll 4
            for (int i = 0; i < 16; i++) g_part[(((b * 16 + i) * 4 + (lane >> 3)) * 16 + ki) * 8 + (lane & 7)] = z;
            __syncwarp();
            if (lane == 0) {
                arrive_and_wait(scr->cnt, 128);
                mbar_arrive(bars + BAR_OK);
            }
        }
        __syncwarp();
        asm volatile("barrier.cluster.wait.acquire.aligned;" ::: "memory");
    } else {
        asm volatile("setmaxnreg.inc.sync.aligned.u32 232;");
        const int g = lane >> 2, t = lane & 3;
        const int mi = lane >> 3, r8 = lane & 7;
        mbar_wait(bars + BAR_WQ, 0);

        {
            float acc[4][4];
#pragma unroll
            for (int nt = 0; nt < 4; nt++) { acc[nt][0] = acc[nt][1] = acc[nt][2] = acc[nt][3] = 0.f; }
            const uint32_t wa = sb + SM_A + ((warp >> 1) * 128 + lane) * 64;
            const uint32_t xa = sb + X_SLOT * STAGE_BYTES + (warp >> 1) * 8192 + ((warp & 1) * 16 + (mi & 1) * 8 + r8) * 128;
#pragma unroll
            for (int i = 0; i < 4; i++) {
                uint32_t a0[4], a1[4];
                ldsm4(a0, xa + (i >> 1) * 4096 + ((((i & 1) * 4 + (mi >> 1)) ^ r8) << 4));
                ldsm4(a1, xa + (i >> 1) * 4096 + ((((i & 1) * 4 + 2 + (mi >> 1)) ^ r8) << 4));
#pragma unroll
                for (int nt = 0; nt < 4; nt++) {
                    uint32_t bw[4];
                    ldsm4t(bw, wa + i * 2048 + ((nt ^ (r8 >> 1)) << 4));
                    mma16816(acc[nt], a0[0], a0[1], a0[2], a0[3], bw[0], bw[1]);
                    mma16816(acc[nt], a1[0], a1[1], a1[2], a1[3], bw[2], bw[3]);
                }
            }
            float4* red = reinterpret_cast<float4*>(smem + SM_A + 32768);
#pragma unroll
            for (int hf = 0; hf < 2; hf++) {
                const int idx = (warp >> 1) * 256 + ((warp & 1) * 16 + hf * 8 + g) * 4 + t;
                red[idx] = make_float4(acc[0][2 * hf], acc[0][2 * hf + 1], acc[1][2 * hf], acc[1][2 * hf + 1]);
                red[idx + 128] = make_float4(acc[2][2 * hf], acc[2][2 * hf + 1], acc[3][2 * hf], acc[3][2 * hf + 1]);
            }
            bar_compute();
            if (tid < 128) {
                uint32_t w[4];
#pragma unroll
                for (int hf = 0; hf < 2; hf++) {
                    const float4 v0 = red[hf * 128 + tid], v1 = red[256 + hf * 128 + tid], v2 = red[512 + hf * 128 + tid], v3 = red[768 + hf * 128 + tid];
                    w[2 * hf] = nz(pack_bf16((v0.x + v1.x) + (v2.x + v3.x), (v0.y + v1.y) + (v2.y + v3.y)));
                    w[2 * hf + 1] = nz(pack_bf16((v0.z + v1.z) + (v2.z + v3.z), (v0.w + v1.w) + (v2.w + v3.w)));
                }
                st_relaxed_v4(&g_q[(((tid >> 4) * 8 + hkv) * 16 + b * 2 + r) * 16 + (tid & 15)], w);
            }
        }
        uint4 qf[8];
        {
            const uint4* qsrc = &g_q[pair * 256 + tid];
            bar_compute();
            if (tid == 0) mbar_arrive(bars + BAR_AFREE);
            spin_clocks(clock64(), Q_DELAY);
            uint4 w = ld_relaxed_v4(qsrc);
            int it = 0;
            while (!valid4(w)) {
                w = ld_relaxed_v4(qsrc);
                if (++it > SPIN_LIMIT) give_up();
            }
            uint4* qs = reinterpret_cast<uint4*>(smem + SM_A + 49152);
            qs[tid] = w;
            bar_compute();
#pragma unroll
            for (int i = 0; i < 8; i++) qf[i] = qs[((g >> 2) * 4 + (i & 1) * 8 + (i >> 1)) * 16 + (g & 3) * 4 + t];
        }

        float S[16][4];
        {
            const uint32_t ka = sb + (warp * 8 + r8) * 128;
#pragma unroll
            for (int n = 0; n < 16; n++) {
                const int s = tile_slot(n);
                mbar_wait(bars + BAR_FULL + 8 * s, tile_par(n));
                float e[4] = {0.f, 0.f, 0.f, 0.f}, o[4] = {0.f, 0.f, 0.f, 0.f};
#pragma unroll
                for (int i = 0; i < 4; i++) {
                    uint32_t kf[4];
                    ldsm4(kf, ka + s * STAGE_BYTES + (i >> 1) * 8192 + (((((i & 1) << 2) + mi) ^ r8) << 4));
                    mma16816(e, qf[2 * i].x, qf[2 * i + 1].x, qf[2 * i].y, qf[2 * i + 1].y, kf[0], kf[1]);
                    mma16816(o, qf[2 * i].z, qf[2 * i + 1].z, qf[2 * i].w, qf[2 * i + 1].w, kf[2], kf[3]);
                }
#pragma unroll
                for (int i = 0; i < 4; i++) S[n][i] = e[i] + o[i];
                if (s < NSTAGE) {
                    __syncwarp();
                    if (lane == 0) mbar_arrive(bars + BAR_EMPTY + 8 * s);
                }
            }
        }

        asm volatile("barrier.cluster.wait.acquire.aligned;" ::: "memory");
        uint32_t peer;
        asm("mapa.shared::cluster.u32 %0, %1, %2;" : "=r"(peer) : "r"(sb), "r"(r ^ 1));
        float inv0, inv1;
        {
            float m0 = fmaxf(S[0][0], S[0][1]), m1 = fmaxf(S[0][2], S[0][3]);
#pragma unroll
            for (int n = 1; n < 16; n++) { m0 = fmaxf(m0, fmaxf(S[n][0], S[n][1])); m1 = fmaxf(m1, fmaxf(S[n][2], S[n][3])); }
            m0 = fmaxf(m0, __shfl_xor_sync(0xffffffffu, m0, 1)); m1 = fmaxf(m1, __shfl_xor_sync(0xffffffffu, m1, 1));
            m0 = fmaxf(m0, __shfl_xor_sync(0xffffffffu, m0, 2)); m1 = fmaxf(m1, __shfl_xor_sync(0xffffffffu, m1, 2));
            const uint32_t off = (uint32_t)(((t & 1) * 8 + g) * 16 + r * 8 + warp) * 4;
            const float mv = (t & 1) ? m1 : m0;
            if (t & 2) asm volatile("st.async.shared::cluster.mbarrier::complete_tx::bytes.f32 [%0], %1, [%2];"
                                    :: "r"(peer + SM_MX + off), "f"(mv), "r"(peer + SM_BAR + BAR_MX) : "memory");
            else asm volatile("st.shared.f32 [%0], %1;" :: "r"(sb + SM_MX + off), "f"(mv) : "memory");
            __syncwarp();
            if (lane == 0) mbar_arrive(bars + BAR_MX);
            mbar_wait_cluster(bars + BAR_MX, 0);
            if (tid < 128) g_q[pair * 256 + r * 128 + tid] = make_uint4(0u, 0u, 0u, 0u);
            const float4* mx = reinterpret_cast<const float4*>(smem + SM_MX);
            const float4 u0 = mx[g * 4 + t], u1 = mx[(g + 8) * 4 + t];
            m0 = fmaxf(fmaxf(u0.x, u0.y), fmaxf(u0.z, u0.w));
            m1 = fmaxf(fmaxf(u1.x, u1.y), fmaxf(u1.z, u1.w));
            m0 = fmaxf(m0, __shfl_xor_sync(0xffffffffu, m0, 1)); m1 = fmaxf(m1, __shfl_xor_sync(0xffffffffu, m1, 1));
            m0 = fmaxf(m0, __shfl_xor_sync(0xffffffffu, m0, 2)); m1 = fmaxf(m1, __shfl_xor_sync(0xffffffffu, m1, 2));
            const float c = 0.08838834764831845f * 1.4426950408889634f;
            float l0 = 0.f, l1 = 0.f;
            const uint32_t poff = SM_A + (r * 8 + warp) * 4096 + lane * 16;
#pragma unroll
            for (int u = 0; u < 8; u++) {
                float p[8];
#pragma unroll
                for (int i = 0; i < 8; i++) p[i] = ex2((S[2 * u + (i >> 2)][i & 3] - ((i & 2) ? m1 : m0)) * c);
                l0 += (p[0] + p[1]) + (p[4] + p[5]);
                l1 += (p[2] + p[3]) + (p[6] + p[7]);
                sts128(sb + poff + u * 512, make_uint4(pack_bf16(p[0], p[1]), pack_bf16(p[2], p[3]), pack_bf16(p[4], p[5]), pack_bf16(p[6], p[7])));
            }
            asm volatile("fence.proxy.async.shared::cta;" ::: "memory");
            __syncwarp();
            if (lane == 0)
                asm volatile("cp.async.bulk.shared::cluster.shared::cta.mbarrier::complete_tx::bytes [%0], [%1], %2, [%3];"
                             :: "r"(peer + poff), "r"(sb + poff), "r"(4096), "r"(peer + SM_BAR + BAR_P) : "memory");
            l0 += __shfl_xor_sync(0xffffffffu, l0, 1); l1 += __shfl_xor_sync(0xffffffffu, l1, 1);
            l0 += __shfl_xor_sync(0xffffffffu, l0, 2); l1 += __shfl_xor_sync(0xffffffffu, l1, 2);
            const float lv = (t & 1) ? l1 : l0;
            if (t & 2) asm volatile("st.async.shared::cluster.mbarrier::complete_tx::bytes.f32 [%0], %1, [%2];"
                                    :: "r"(peer + SM_LS + off), "f"(lv), "r"(peer + SM_BAR + BAR_P) : "memory");
            else asm volatile("st.shared.f32 [%0], %1;" :: "r"(sb + SM_LS + off), "f"(lv) : "memory");
            __syncwarp();
            if (lane == 0) mbar_arrive(bars + BAR_P);
            mbar_wait_cluster(bars + BAR_P, 0);
            const float4* ls = reinterpret_cast<const float4*>(smem + SM_LS);
            const float4 v0 = ls[g * 4 + t], v1 = ls[(g + 8) * 4 + t];
            l0 = (v0.x + v0.y) + (v0.z + v0.w);
            l1 = (v1.x + v1.y) + (v1.z + v1.w);
            l0 += __shfl_xor_sync(0xffffffffu, l0, 1); l1 += __shfl_xor_sync(0xffffffffu, l1, 1);
            l0 += __shfl_xor_sync(0xffffffffu, l0, 2); l1 += __shfl_xor_sync(0xffffffffu, l1, 2);
            inv0 = 1.f / l0; inv1 = 1.f / l1;
        }

        const int mp = warp & 1, nt = warp >> 1;
        const int po = nt * 256 + (lane >> 4) * 32 + mp * 16 + (lane & 15);
        uint32_t o_dst_off = offsetof(Scratch, o) + 8 * ((((ki * 4 + (b >> 1)) * 8 + warp) * 32 + ((b & 1) * 4 + (g & 3)) * 4 + t) * 2 + (g >> 2));
        uint32_t o_src_off = offsetof(Scratch, o) + 16 * (ki * 1024 + po);
        uint32_t p_dst_off = offsetof(Scratch, part) + 16 * ((((b * 16 + nt * 4 + t) * 4 + mp * 2) * 16 + ki) * 8 + g);
        unsigned char* const sc = reinterpret_cast<unsigned char*>(scr);
        uint32_t os_st = sb + tile_slot(O_TILE) * STAGE_BYTES + po * 16;
        uint32_t os_ld = sb + tile_slot(O_TILE) * STAGE_BYTES + (nt * 256 + lane) * 16;
        uint32_t wa0 = sb + (mi >> 1) * 4096 + r8 * 128 + (((mp * 4 + (mi & 1)) ^ r8) << 4);
        uint32_t wa1 = sb + (mi >> 1) * 4096 + r8 * 128 + (((mp * 4 + 2 + (mi & 1)) ^ r8) << 4);
        uint32_t va = sb + ((mi & 1) * 64 + (mi >> 1) * 8 + r8) * 128 + ((warp ^ r8) << 4);
        uint32_t pa = sb + SM_A + lane * 16;
        uint32_t tb = bars;
        asm volatile("" : "+r"(o_dst_off), "+r"(o_src_off), "+r"(p_dst_off));
        asm volatile("" : "+r"(os_st), "+r"(os_ld), "+r"(wa0), "+r"(wa1), "+r"(va), "+r"(pa), "+r"(tb));

        float oa[4][4];
#pragma unroll
        for (int i = 0; i < 4; i++) { oa[i][0] = oa[i][1] = oa[i][2] = oa[i][3] = 0.f; }
        auto pv_tile = [&](int v, int s, uint32_t ph) {
            uint4 p[8];
#pragma unroll
            for (int j = 0; j < 8; j++) p[j] = lds128(pa + ((v >> 3) * 64 + (v & 7)) * 512 + j * 4096);
            const uint32_t vs = va + s * STAGE_BYTES;
            mbar_wait(tb + BAR_FULL + 8 * s, ph);
#pragma unroll
            for (int j2 = 0; j2 < 4; j2++) {
                uint32_t vf[4];
                ldsm4t(vf, vs + j2 * 2048);
                mma16816(oa[(2 * j2) & 3], p[2 * j2].x, p[2 * j2].y, p[2 * j2].z, p[2 * j2].w, vf[0], vf[1]);
                mma16816(oa[(2 * j2 + 1) & 3], p[2 * j2 + 1].x, p[2 * j2 + 1].y, p[2 * j2 + 1].z, p[2 * j2 + 1].w, vf[2], vf[3]);
            }
        };
        {
            int s = tile_slot(16);
            uint32_t ph = tile_par(16);
#pragma unroll 1
            for (int v = 0; v < 15; v++) {
                pv_tile(v, s, ph);
                __syncwarp();
                if (lane == 0) mbar_arrive(tb + BAR_EMPTY + 8 * s);
                if (++s == NSTAGE) { s = 0; ph ^= 1; }
            }
        }
        mbar_wait(tb + BAR_OK, 0);
        mbar_wait(tb + BAR_EMPTY + 8 * tile_slot(O_TILE), tile_par(O_TILE));
        pv_tile(15, tile_slot(31), tile_par(31));
        {
            const float o0 = ((oa[0][0] + oa[1][0]) + (oa[2][0] + oa[3][0])) * inv0;
            const float o1 = ((oa[0][1] + oa[1][1]) + (oa[2][1] + oa[3][1])) * inv0;
            const float o2 = ((oa[0][2] + oa[1][2]) + (oa[2][2] + oa[3][2])) * inv1;
            const float o3 = ((oa[0][3] + oa[1][3]) + (oa[2][3] + oa[3][3])) * inv1;
            asm volatile("red.relaxed.gpu.global.or.b64 [%0], %1;"
                         :: "l"(sc + o_dst_off), "l"((uint64_t)nz(pack_bf16(o0, o1)) | (uint64_t)nz(pack_bf16(o2, o3)) << 32) : "memory");
        }

        {
            spin_clocks(clock64(), O_DELAY);
            const uint4* o_src = reinterpret_cast<const uint4*>(sc + o_src_off);
            uint4 og[4];
#pragma unroll
            for (int j = 0; j < 4; j++) og[j] = ld_relaxed_v4(o_src + j * 64);
            const uint32_t ob = tb + BAR_O + 8 * nt;
            bool done = false;
            int it = 0;
            auto poll = [&]() {
                bool ok = true;
#pragma unroll
                for (int j = 0; j < 4; j++) {
                    if (!valid4(og[j])) { og[j] = ld_relaxed_v4(o_src + j * 64); ok = false; }
                }
                if (__all_sync(0xffffffffu, ok)) {
#pragma unroll
                    for (int j = 0; j < 4; j++) sts128(os_st + j * 1024, og[j]);
                    __syncwarp();
                    if (lane == 0) mbar_arrive(ob);
                    done = true;
                }
            };
            uint32_t wf[4][8][4];
            auto load_wo = [&](int qd) {
#pragma unroll
                for (int k = 0; k < 4; k++) {
                    const uint32_t a = tile_slot(32 + (qd >> 1)) * STAGE_BYTES + (qd & 1) * 8192 + (k & 1) * 2048 + (k >> 1) * 1024;
                    ldsm4t(wf[qd][2 * k], wa0 + a);
                    ldsm4t(wf[qd][2 * k + 1], wa1 + a);
                }
            };
            bool have[4];
#pragma unroll
            for (int qd = 0; qd < 4; qd++) {
                while (true) {
                    have[qd] = mbar_test(tb + BAR_WO + 8 * qd, 0);
                    if (have[qd]) break;
                    if (!done) poll();
                    else if (mbar_test(ob, 0)) break;
                    if (++it > SPIN_LIMIT) give_up();
                }
                if (have[qd]) load_wo(qd);
            }
            while (!done) {
                poll();
                if (++it > SPIN_LIMIT) give_up();
            }
            mbar_wait(ob, 0);
            uint4 of[8];
#pragma unroll
            for (int w = 0; w < 8; w++) of[w] = lds128(os_ld + w * 512);
            float acc[2][4][4];
#pragma unroll
            for (int i = 0; i < 16; i++) { acc[0][i >> 2][i & 3] = acc[1][i >> 2][i & 3] = 0.f; }
#pragma unroll
            for (int qd = 0; qd < 4; qd++) {
                if (!have[qd]) {
                    mbar_wait(tb + BAR_WO + 8 * qd, 0);
                    load_wo(qd);
                }
#pragma unroll
                for (int k = 0; k < 4; k++) {
                    const uint4& o4 = of[qd * 2 + (k >> 1)];
                    const uint32_t b0 = (k & 1) ? o4.z : o4.x, b1 = (k & 1) ? o4.w : o4.y;
                    mma16816(acc[0][k], wf[qd][2 * k][0], wf[qd][2 * k][1], wf[qd][2 * k][2], wf[qd][2 * k][3], b0, b1);
                    mma16816(acc[1][k], wf[qd][2 * k + 1][0], wf[qd][2 * k + 1][1], wf[qd][2 * k + 1][2], wf[qd][2 * k + 1][3], b0, b1);
                }
            }
#pragma unroll
            for (int mt = 0; mt < 2; mt++) {
                uint32_t w[4];
#pragma unroll
                for (int i = 0; i < 4; i++) w[i] = nz(__float_as_uint((acc[mt][0][i] + acc[mt][1][i]) + (acc[mt][2][i] + acc[mt][3][i])));
                st_relaxed_v4(sc + p_dst_off + mt * 2048, w);
            }
        }

        {
            const long long t0 = clock64();
            const uint4* p_src = &g_part[(((b * 16 + ki) * 4 + nt) * 16 + g) * 8 + mp * 4 + t];
            __nv_bfloat16* out_dst = out + (2 * ki + (g & 1)) * 512 + b * 64 + nt * 16 + mp * 4 + t + (g & 2) * 4;
            asm volatile("" : "+l"(p_src), "+l"(out_dst));
            spin_clocks(t0, PART_DELAY);
            uint4 u0 = ld_relaxed_v4(p_src), u1 = ld_relaxed_v4(p_src + 64);
            int it = 0;
            while (true) {
                bool ok = true;
                if (!valid4(u0)) { u0 = ld_relaxed_v4(p_src); ok = false; }
                if (!valid4(u1)) { u1 = ld_relaxed_v4(p_src + 64); ok = false; }
                if (__all_sync(0xffffffffu, ok)) break;
                if (++it > SPIN_LIMIT) give_up();
            }
            float v0 = __uint_as_float(u0.x) + __uint_as_float(u1.x);
            float v1 = __uint_as_float(u0.y) + __uint_as_float(u1.y);
            float v2 = __uint_as_float(u0.z) + __uint_as_float(u1.z);
            float v3 = __uint_as_float(u0.w) + __uint_as_float(u1.w);
#pragma unroll
            for (int d = 4; d < 32; d <<= 1) {
                v0 += __shfl_xor_sync(0xffffffffu, v0, d);
                v1 += __shfl_xor_sync(0xffffffffu, v1, d);
                v2 += __shfl_xor_sync(0xffffffffu, v2, d);
                v3 += __shfl_xor_sync(0xffffffffu, v3, d);
            }
            if (lane < 16) *out_dst = __float2bfloat16_rn((g & 2) ? ((g & 1) ? v3 : v2) : ((g & 1) ? v1 : v0));
        }
    }
}

typedef CUresult (*EncodeTiledFn)(CUtensorMap*, CUtensorMapDataType, cuuint32_t, void*, const cuuint64_t*, const cuuint64_t*,
                                  const cuuint32_t*, const cuuint32_t*, CUtensorMapInterleave, CUtensorMapSwizzle,
                                  CUtensorMapL2promotion, CUtensorMapFloatOOBfill);

void encode3d(EncodeTiledFn enc, CUtensorMap* tm, const void* base, cuuint64_t d0, cuuint64_t d1, cuuint64_t d2,
              cuuint64_t s1, cuuint64_t s2, cuuint32_t b0, cuuint32_t b1, cuuint32_t b2,
              CUtensorMapSwizzle sw = CU_TENSOR_MAP_SWIZZLE_128B) {
    const cuuint64_t dims[3] = {d0, d1, d2};
    const cuuint64_t strides[2] = {s1, s2};
    const cuuint32_t box[3] = {b0, b1, b2};
    const cuuint32_t es[3] = {1, 1, 1};
    enc(tm, CU_TENSOR_MAP_DATA_TYPE_BFLOAT16, 3, const_cast<void*>(base), dims, strides, box, es,
        CU_TENSOR_MAP_INTERLEAVE_NONE, sw, CU_TENSOR_MAP_L2_PROMOTION_L2_256B, CU_TENSOR_MAP_FLOAT_OOB_FILL_NONE);
}

}

extern "C" void kernel_launch(void* const* d_in, const int* in_sizes, int n_in, void* d_out, int out_size) {
    (void)in_sizes; (void)n_in; (void)out_size;
    const __nv_bfloat16* x = (const __nv_bfloat16*)d_in[0];
    const __nv_bfloat16* kc = (const __nv_bfloat16*)d_in[1];
    const __nv_bfloat16* vc = (const __nv_bfloat16*)d_in[2];
    const __nv_bfloat16* wq = (const __nv_bfloat16*)d_in[3];
    const __nv_bfloat16* wo = (const __nv_bfloat16*)d_in[4];

    static EncodeTiledFn enc = nullptr;
    static Scratch* scr = nullptr;
    if (!enc) {
        cudaGetSymbolAddress((void**)&scr, g_scratch);
        void* fn = nullptr;
        cudaDriverEntryPointQueryResult st;
        cudaGetDriverEntryPoint("cuTensorMapEncodeTiled", &fn, cudaEnableDefault, &st);
        enc = (EncodeTiledFn)fn;
        cudaFuncSetAttribute(gqa_fused_kernel, cudaFuncAttributeMaxDynamicSharedMemorySize, SM_TOTAL);
    }
    CUtensorMap tmK, tmV, tmWo, tmWq, tmX;
    encode3d(enc, &tmK, kc, 64, 131072, 2, 256, 128, 64, 64, 2);
    encode3d(enc, &tmV, vc, 64, 131072, 2, 256, 128, 64, 128, 1);
    encode3d(enc, &tmWo, wo, 512, 128, 32, 1024, 131072, 64, 16, 2);
    encode3d(enc, &tmWq, wq, 4096, 256, 2, 8192, 256 * 8192, 32, 256, 2, CU_TENSOR_MAP_SWIZZLE_64B);
    encode3d(enc, &tmX, x, 64, 32, 8, 1024, 128, 64, 32, 8);
    gqa_fused_kernel<<<128, NTHREADS, SM_TOTAL, cudaStreamPerThread>>>(wq, x, (__nv_bfloat16*)d_out, scr, tmK, tmV, tmWo, tmWq, tmX);
}
```

```cpp
#include <cuda_runtime.h>
#include <cuda.h>
#include <cuda_bf16.h>
#include <stdint.h>
#include <stddef.h>

namespace {

constexpr int NSTAGE = 10;
constexpr int STAGE_BYTES = 16384;
constexpr int NTHREADS = 384;

constexpr int W0 = 2;
constexpr uint32_t T_FIRST = 1600;
constexpr uint32_t T_TILE = 645;
constexpr int WINDOW = 6;
constexpr uint32_t T_WO = 21900;
constexpr uint32_t T_WO_PIECE = 170;
constexpr int Q_DELAY = 4000;
constexpr int O_DELAY = 250;
constexpr int PART_DELAY = 400;

constexpr int SM_A = NSTAGE * STAGE_BYTES;
constexpr int SM_BAR = SM_A + 65536;
constexpr int SM_MX = SM_BAR + 320;
constexpr int SM_LS = SM_MX + 1024;
constexpr int SM_TOTAL = SM_LS + 1024;

constexpr int BAR_FULL = 0;
constexpr int BAR_EMPTY = BAR_FULL + 8 * 13;
constexpr int BAR_WO = BAR_EMPTY + 8 * NSTAGE;
constexpr int BAR_MX = BAR_WO + 32;
constexpr int BAR_P = BAR_MX + 8;
constexpr int BAR_OK = BAR_P + 8;
constexpr int BAR_WQ = BAR_OK + 8;
constexpr int BAR_AFREE = BAR_WQ + 8;
constexpr int BAR_O = BAR_AFREE + 8;
constexpr int BAR_END = BAR_O + 32;
static_assert(BAR_END <= 320, "barrier area");

__host__ __device__ constexpr int tile_seq(int n) { return n < 10 ? n : n - 3; }
__host__ __device__ constexpr int tile_slot(int n) { return (n >= 10 && n < 13) ? n : tile_seq(n) % NSTAGE; }
__host__ __device__ constexpr int tile_par(int n) { return (n >= 10 && n < 13) ? 0 : (tile_seq(n) / NSTAGE) & 1; }
constexpr int X_SLOT = 8;
constexpr int O_TILE = 24;

constexpr int SPIN_LIMIT = 1 << 20;

struct Scratch {
    uint4 q[64 * 16 * 16];
    uint4 o[16 * 4 * 8 * 32];
    uint4 part[8 * 16 * 4 * 16 * 8];
    unsigned int cnt[32];
};
__device__ Scratch g_scratch;

__device__ __forceinline__ uint32_t smem_u32(const void* p) { return (uint32_t)__cvta_generic_to_shared(p); }
__device__ __forceinline__ void give_up() {
    asm volatile("st.volatile.global.u32 [%0], %1;\n\texit;" :: "l"(0ull), "r"(0) : "memory");
}
__device__ __forceinline__ uint32_t now_ns() {
    uint32_t t;
    asm volatile("mov.u32 %0, %%globaltimer_lo;" : "=r"(t));
    return t;
}
__device__ __forceinline__ void wait_until(uint32_t due) {
    for (int i = 0; i < (1 << 16) && (int)(now_ns() - due) < 0; i++) {}
}
__device__ __forceinline__ void spin_clocks(long long t0, int n) { while (clock64() - t0 < n) {} }
__device__ __forceinline__ void mbar_init(uint32_t bar, uint32_t count) {
    asm volatile("mbarrier.init.shared::cta.b64 [%0], %1;" :: "r"(bar), "r"(count) : "memory");
}
__device__ __forceinline__ void mbar_expect_tx(uint32_t bar, uint32_t bytes) {
    asm volatile("mbarrier.arrive.expect_tx.shared::cta.b64 _, [%0], %1;" :: "r"(bar), "r"(bytes) : "memory");
}
__device__ __forceinline__ void mbar_arrive(uint32_t bar) {
    asm volatile("mbarrier.arrive.shared::cta.b64 _, [%0];" :: "r"(bar) : "memory");
}
__device__ __forceinline__ void mbar_wait(uint32_t bar, uint32_t parity) {
    uint32_t ok;
    int it = 0;
    do {
        asm volatile("{\n.reg .pred p;\nmbarrier.try_wait.parity.shared::cta.b64 p, [%1], %2;\nselp.u32 %0, 1, 0, p;\n}"
                     : "=r"(ok) : "r"(bar), "r"(parity) : "memory");
        if (++it > SPIN_LIMIT) give_up();
    } while (!ok);
}
__device__ __forceinline__ bool mbar_test(uint32_t bar, uint32_t parity) {
    uint32_t ok;
    asm volatile("{\n.reg .pred p;\nmbarrier.test_wait.parity.shared::cta.b64 p, [%1], %2;\nselp.u32 %0, 1, 0, p;\n}"
                 : "=r"(ok) : "r"(bar), "r"(parity) : "memory");
    return __all_sync(0xffffffffu, ok != 0);
}
__device__ __forceinline__ void mbar_wait_cluster(uint32_t bar, uint32_t parity) {
    uint32_t ok;
    int it = 0;
    do {
        asm volatile("{\n.reg .pred p;\nmbarrier.try_wait.parity.acquire.cluster.shared::cta.b64 p, [%1], %2;\nselp.u32 %0, 1, 0, p;\n}"
                     : "=r"(ok) : "r"(bar), "r"(parity) : "memory");
        if (++it > SPIN_LIMIT) give_up();
    } while (!ok);
}
__device__ __forceinline__ void tma3d(uint32_t dst, const CUtensorMap* tm, int c0, int c1, int c2, uint32_t bar) {
    asm volatile("cp.async.bulk.tensor.3d.shared::cluster.global.mbarrier::complete_tx::bytes [%0], [%1, {%3, %4, %5}], [%2];"
                 :: "r"(dst), "l"(tm), "r"(bar), "r"(c0), "r"(c1), "r"(c2) : "memory");
}
__device__ __forceinline__ void tma3d_hint(uint32_t dst, const CUtensorMap* tm, int c0, int c1, int c2, uint32_t bar, uint64_t pol) {
    asm volatile("cp.async.bulk.tensor.3d.shared::cluster.global.mbarrier::complete_tx::bytes.L2::cache_hint [%0], [%1, {%3, %4, %5}], [%2], %6;"
                 :: "r"(dst), "l"(tm), "r"(bar), "r"(c0), "r"(c1), "r"(c2), "l"(pol) : "memory");
}
__device__ __forceinline__ void ldsm4(uint32_t (&r)[4], uint32_t addr) {
    asm volatile("ldmatrix.sync.aligned.m8n8.x4.shared.b16 {%0, %1, %2, %3}, [%4];"
                 : "=r"(r[0]), "=r"(r[1]), "=r"(r[2]), "=r"(r[3]) : "r"(addr) : "memory");
}
__device__ __forceinline__ void ldsm4t(uint32_t (&r)[4], uint32_t addr) {
    asm volatile("ldmatrix.sync.aligned.m8n8.x4.trans.shared.b16 {%0, %1, %2, %3}, [%4];"
                 : "=r"(r[0]), "=r"(r[1]), "=r"(r[2]), "=r"(r[3]) : "r"(addr) : "memory");
}
__device__ __forceinline__ void mma16816(float (&c)[4], uint32_t a0, uint32_t a1, uint32_t a2, uint32_t a3, uint32_t b0, uint32_t b1) {
    asm volatile("mma.sync.aligned.m16n8k16.row.col.f32.bf16.bf16.f32 {%0, %1, %2, %3}, {%4, %5, %6, %7}, {%8, %9}, {%0, %1, %2, %3};"
                 : "+f"(c[0]), "+f"(c[1]), "+f"(c[2]), "+f"(c[3]) : "r"(a0), "r"(a1), "r"(a2), "r"(a3), "r"(b0), "r"(b1));
}
__device__ __forceinline__ uint32_t pack_bf16(float lo, float hi) {
    uint32_t r;
    asm("cvt.rn.bf16x2.f32 %0, %1, %2;" : "=r"(r) : "f"(hi), "f"(lo));
    return r;
}
__device__ __forceinline__ float bf16_lo(uint32_t d) { return __uint_as_float(d << 16); }
__device__ __forceinline__ float bf16_hi(uint32_t d) { return __uint_as_float(d & 0xffff0000u); }
__device__ __forceinline__ uint32_t max_bf16x2(uint32_t a, uint32_t b) {
    uint32_t r;
    asm("max.bf16x2 %0, %1, %2;" : "=r"(r) : "r"(a), "r"(b));
    return r;
}
__device__ __forceinline__ float ex2(float x) {
    float r;
    asm("ex2.approx.ftz.f32 %0, %1;" : "=f"(r) : "f"(x));
    return r;
}
__device__ __forceinline__ uint4 ld_relaxed_v4(const uint4* p) {
    uint4 v;
    asm volatile("ld.relaxed.gpu.global.v4.u32 {%0, %1, %2, %3}, [%4];" : "=r"(v.x), "=r"(v.y), "=r"(v.z), "=r"(v.w) : "l"(p) : "memory");
    return v;
}
__device__ __forceinline__ void st_relaxed_v4(void* p, const uint32_t (&w)[4]) {
    asm volatile("st.relaxed.gpu.global.v4.u32 [%0], {%1, %2, %3, %4};" :: "l"(p), "r"(w[0]), "r"(w[1]), "r"(w[2]), "r"(w[3]) : "memory");
}
__device__ __forceinline__ uint4 lds128(uint32_t a) {
    uint4 v;
    asm volatile("ld.shared.v4.u32 {%0, %1, %2, %3}, [%4];" : "=r"(v.x), "=r"(v.y), "=r"(v.z), "=r"(v.w) : "r"(a) : "memory");
    return v;
}
__device__ __forceinline__ void sts128(uint32_t a, const uint4& v) {
    asm volatile("st.shared.v4.u32 [%0], {%1, %2, %3, %4};" :: "r"(a), "r"(v.x), "r"(v.y), "r"(v.z), "r"(v.w) : "memory");
}
__device__ __forceinline__ uint32_t nz(uint32_t w) { return w == 0u ? 0x80000000u : w; }
__device__ __forceinline__ bool valid4(const uint4& v) { return v.x != 0u && v.y != 0u && v.z != 0u && v.w != 0u; }
__device__ __forceinline__ void bar_compute() { asm volatile("bar.sync 1, 256;" ::: "memory"); }

__device__ __forceinline__ void arrive_and_wait(unsigned int* cnt, unsigned int n) {
    unsigned int old;
    asm volatile("atom.add.release.gpu.global.u32 %0, [%1], 1;" : "=r"(old) : "l"(cnt) : "memory");
    const unsigned int target = (old | (n - 1)) + 1;
    unsigned int cur;
    int it = 0;
    do {
        asm volatile("ld.acquire.gpu.global.u32 %0, [%1];" : "=r"(cur) : "l"(cnt) : "memory");
        if (++it > SPIN_LIMIT) give_up();
    } while ((int)(cur - target) < 0);
}

__global__ void __cluster_dims__(2, 1, 1) __launch_bounds__(NTHREADS, 1)
gqa_fused_kernel(const __nv_bfloat16* __restrict__ wq, const __nv_bfloat16* __restrict__ x, __nv_bfloat16* __restrict__ out,
                 Scratch* __restrict__ scr,
                 const __grid_constant__ CUtensorMap tmK, const __grid_constant__ CUtensorMap tmV,
                 const __grid_constant__ CUtensorMap tmWo, const __grid_constant__ CUtensorMap tmWq,
                 const __grid_constant__ CUtensorMap tmX) {
    extern __shared__ __align__(1024) unsigned char smem[];
    const int tid = threadIdx.x;
    uint4* const g_q = scr->q;
    uint4* const g_o = scr->o;
    uint4* const g_part = scr->part;
    const uint32_t sb = smem_u32(smem);
    const uint32_t bars = sb + SM_BAR;
    const int warp = tid >> 5, lane = tid & 31;
    const int r = blockIdx.x & 1;
    const int pair = blockIdx.x >> 1;
    const int b = pair >> 3, hkv = pair & 7;
    const int krow = blockIdx.x * 1024;
    uint64_t pol;
    asm volatile("createpolicy.fractional.L2::evict_first.b64 %0, 1.0;" : "=l"(pol));
    const uint32_t t_start = now_ns();

    if (tid == 0) {
        asm volatile("cp.async.bulk.prefetch.L2.global [%0], %1;" :: "l"(x + blockIdx.x * 128), "r"(256) : "memory");
        asm volatile("cp.async.bulk.prefetch.L2.global [%0], %1;" :: "l"(wq + blockIdx.x * 16384), "r"(32768) : "memory");
        mbar_init(bars + BAR_WQ, 1);
#pragma unroll
        for (int n = 0; n < W0; n++) mbar_init(bars + BAR_FULL + 8 * n, 1);
        asm volatile("fence.proxy.async.shared::cta;" ::: "memory");
        mbar_expect_tx(bars + BAR_WQ, 65536);
        tma3d(sb + X_SLOT * STAGE_BYTES, &tmX, 0, 0, 0, bars + BAR_WQ);
        tma3d(sb + SM_A, &tmWq, hkv * 512 + (b * 2 + r) * 32, 0, 0, bars + BAR_WQ);
#pragma unroll
        for (int n = 0; n < W0; n++) {
            mbar_expect_tx(bars + BAR_FULL + 8 * n, STAGE_BYTES);
            tma3d_hint(sb + n * STAGE_BYTES, &tmK, 0, krow + n * 64, 0, bars + BAR_FULL + 8 * n, pol);
        }
#pragma unroll
        for (int off = 8 * W0; off < BAR_END; off += 8)
            if (off != BAR_WQ)
                mbar_init(bars + off, off < BAR_EMPTY ? 1 : off < BAR_WO ? 8 : off < BAR_MX ? 1 : off < BAR_OK ? 9 : off >= BAR_O ? 2 : 1);
        mbar_expect_tx(bars + BAR_MX, 512);
        mbar_expect_tx(bars + BAR_P, 32768 + 512);
        asm volatile("fence.mbarrier_init.release.cluster;" ::: "memory");
        asm volatile("fence.proxy.async.shared::cta;" ::: "memory");
    }
    __syncwarp();
    asm volatile("barrier.cluster.arrive.relaxed.aligned;" ::: "memory");
    __syncthreads();

    const int ki = hkv * 2 + r;
    if (__shfl_sync(0xffffffffu, tid >> 7, 0) == 2) {
        asm volatile("setmaxnreg.dec.sync.aligned.u32 40;");
        if (warp == 8) {
            if (lane == 0) {
                asm volatile("prefetch.tensormap [%0];" :: "l"(&tmV) : "memory");
                asm volatile("prefetch.tensormap [%0];" :: "l"(&tmWo) : "memory");
                uint32_t due = t_start + T_FIRST;
#pragma unroll 1
                for (int n = W0; n < 32; n++) {
                    wait_until(due);
                    due += T_TILE;
                    if (n >= WINDOW) mbar_wait(bars + BAR_FULL + 8 * tile_slot(n - WINDOW), tile_par(n - WINDOW));
                    const int s = tile_slot(n);
                    if (n == X_SLOT) mbar_wait(bars + BAR_AFREE, 0);
                    if (n >= 13) mbar_wait(bars + BAR_EMPTY + 8 * s, tile_par(n) ^ 1);
                    const uint32_t dst = sb + s * STAGE_BYTES;
                    const uint32_t fb = bars + BAR_FULL + 8 * s;
                    mbar_expect_tx(fb, STAGE_BYTES);
                    if (n < 16) tma3d_hint(dst, &tmK, 0, krow + n * 64, 0, fb, pol);
                    else tma3d_hint(dst, &tmV, 0, pair * 2048 + (n - 16) * 128, r, fb, pol);
                }
                mbar_wait(bars + BAR_EMPTY + 8 * tile_slot(32), tile_par(32) ^ 1);
                mbar_wait(bars + BAR_EMPTY + 8 * tile_slot(33), tile_par(33) ^ 1);
                mbar_wait(bars + BAR_FULL + 8 * tile_slot(27), tile_par(27));
                due = now_ns();
                if ((int)(due - (t_start + T_WO)) < 0) due = t_start + T_WO;
                due += ((blockIdx.x * 37) & 127) * T_WO_PIECE / 128;
#pragma unroll
                for (int u = 0; u < 8; u++) {
                    const int qd = u >> 1, hh = (u & 1) * 2;
                    wait_until(due);
                    due += T_WO_PIECE;
                    if (hh == 0) mbar_expect_tx(bars + BAR_WO + 8 * qd, 8192);
                    tma3d(sb + tile_slot(32 + (qd >> 1)) * STAGE_BYTES + (qd & 1) * 8192 + hh * 2048, &tmWo,
                          b * 64, r * 64 + qd * 16, hkv * 4 + hh, bars + BAR_WO + 8 * qd);
                }
            }
        } else if (warp == 9) {
            mbar_wait(bars + BAR_AFREE, 0);
            const uint4 z = make_uint4(0u, 0u, 0u, 0u);
#pragma unroll 1
            for (int i = 0; i < 4; i++) g_o[(ki * 4 + (b >> 1)) * 256 + (i * 2 + (lane >> 4)) * 32 + (b & 1) * 16 + (lane & 15)] = z;
#pragma unroll 4
            for (int i = 0; i < 16; i++) g_part[(((b * 16 + i) * 4 + (lane >> 3)) * 16 + ki) * 8 + (lane & 7)] = z;
            __syncwarp();
            if (lane == 0) {
                arrive_and_wait(scr->cnt, 128);
                mbar_arrive(bars + BAR_OK);
            }
        }
        __syncwarp();
        asm volatile("barrier.cluster.wait.acquire.aligned;" ::: "memory");
    } else {
        asm volatile("setmaxnreg.inc.sync.aligned.u32 232;");
        const int g = lane >> 2, t = lane & 3;
        const int mi = lane >> 3, r8 = lane & 7;
        mbar_wait(bars + BAR_WQ, 0);

        {
            float acc[4][4];
#pragma unroll
            for (int nt = 0; nt < 4; nt++) { acc[nt][0] = acc[nt][1] = acc[nt][2] = acc[nt][3] = 0.f; }
            const uint32_t wa = sb + SM_A + ((warp >> 1) * 128 + lane) * 64;
            const uint32_t xa = sb + X_SLOT * STAGE_BYTES + (warp >> 1) * 8192 + ((warp & 1) * 16 + (mi & 1) * 8 + r8) * 128;
#pragma unroll
            for (int i = 0; i < 4; i++) {
                uint32_t a0[4], a1[4];
                ldsm4(a0, xa + (i >> 1) * 4096 + ((((i & 1) * 4 + (mi >> 1)) ^ r8) << 4));
                ldsm4(a1, xa + (i >> 1) * 4096 + ((((i & 1) * 4 + 2 + (mi >> 1)) ^ r8) << 4));
#pragma unroll
                for (int nt = 0; nt < 4; nt++) {
                    uint32_t bw[4];
                    ldsm4t(bw, wa + i * 2048 + ((nt ^ (r8 >> 1)) << 4));
                    mma16816(acc[nt], a0[0], a0[1], a0[2], a0[3], bw[0], bw[1]);
                    mma16816(acc[nt], a1[0], a1[1], a1[2], a1[3], bw[2], bw[3]);
                }
            }
            float4* red = reinterpret_cast<float4*>(smem + SM_A + 32768);
#pragma unroll
            for (int hf = 0; hf < 2; hf++) {
                const int idx = (warp >> 1) * 256 + ((warp & 1) * 16 + hf * 8 + g) * 4 + t;
                red[idx] = make_float4(acc[0][2 * hf], acc[0][2 * hf + 1], acc[1][2 * hf], acc[1][2 * hf + 1]);
                red[idx + 128] = make_float4(acc[2][2 * hf], acc[2][2 * hf + 1], acc[3][2 * hf], acc[3][2 * hf + 1]);
            }
            bar_compute();
            if (tid < 128) {
                uint32_t w[4];
#pragma unroll
                for (int hf = 0; hf < 2; hf++) {
                    const float4 v0 = red[hf * 128 + tid], v1 = red[256 + hf * 128 + tid], v2 = red[512 + hf * 128 + tid], v3 = red[768 + hf * 128 + tid];
                    w[2 * hf] = nz(pack_bf16((v0.x + v1.x) + (v2.x + v3.x), (v0.y + v1.y) + (v2.y + v3.y)));
                    w[2 * hf + 1] = nz(pack_bf16((v0.z + v1.z) + (v2.z + v3.z), (v0.w + v1.w) + (v2.w + v3.w)));
                }
                st_relaxed_v4(&g_q[(((tid >> 4) * 8 + hkv) * 16 + b * 2 + r) * 16 + (tid & 15)], w);
            }
        }
        uint4 qf[8];
        {
            const uint4* qsrc = &g_q[pair * 256 + tid];
            bar_compute();
            if (tid == 0) mbar_arrive(bars + BAR_AFREE);
            spin_clocks(clock64(), Q_DELAY);
            uint4 w = ld_relaxed_v4(qsrc);
            int it = 0;
            while (!valid4(w)) {
                w = ld_relaxed_v4(qsrc);
                if (++it > SPIN_LIMIT) give_up();
            }
            uint4* qs = reinterpret_cast<uint4*>(smem + SM_A + 49152);
            qs[tid] = w;
            bar_compute();
#pragma unroll
            for (int i = 0; i < 8; i++) qf[i] = qs[((g >> 2) * 4 + (i & 1) * 8 + (i >> 1)) * 16 + (g & 3) * 4 + t];
        }

        uint32_t S[16][2];
        {
            const uint32_t ka = sb + (warp * 8 + r8) * 128;
#pragma unroll
            for (int n = 0; n < 16; n++) {
                const int s = tile_slot(n);
                mbar_wait(bars + BAR_FULL + 8 * s, tile_par(n));
                float e[4] = {0.f, 0.f, 0.f, 0.f}, o[4] = {0.f, 0.f, 0.f, 0.f};
#pragma unroll
                for (int i = 0; i < 4; i++) {
                    uint32_t kf[4];
                    ldsm4(kf, ka + s * STAGE_BYTES + (i >> 1) * 8192 + (((((i & 1) << 2) + mi) ^ r8) << 4));
                    mma16816(e, qf[2 * i].x, qf[2 * i + 1].x, qf[2 * i].y, qf[2 * i + 1].y, kf[0], kf[1]);
                    mma16816(o, qf[2 * i].z, qf[2 * i + 1].z, qf[2 * i].w, qf[2 * i + 1].w, kf[2], kf[3]);
                }
#pragma unroll
                for (int i = 0; i < 2; i++) {
                    const uint32_t d = pack_bf16(e[2 * i] + o[2 * i], e[2 * i + 1] + o[2 * i + 1]);
                    S[n][i] = pack_bf16(bf16_lo(d) * 0.08838834764831845f, bf16_hi(d) * 0.08838834764831845f);
                }
                if (s < NSTAGE) {
                    __syncwarp();
                    if (lane == 0) mbar_arrive(bars + BAR_EMPTY + 8 * s);
                }
            }
        }

        asm volatile("barrier.cluster.wait.acquire.aligned;" ::: "memory");
        uint32_t peer;
        asm("mapa.shared::cluster.u32 %0, %1, %2;" : "=r"(peer) : "r"(sb), "r"(r ^ 1));
        float inv0, inv1;
        {
            uint32_t h0 = S[0][0], h1 = S[0][1];
#pragma unroll
            for (int n = 1; n < 16; n++) { h0 = max_bf16x2(h0, S[n][0]); h1 = max_bf16x2(h1, S[n][1]); }
            float m0 = fmaxf(bf16_lo(h0), bf16_hi(h0)), m1 = fmaxf(bf16_lo(h1), bf16_hi(h1));
            m0 = fmaxf(m0, __shfl_xor_sync(0xffffffffu, m0, 1)); m1 = fmaxf(m1, __shfl_xor_sync(0xffffffffu, m1, 1));
            m0 = fmaxf(m0, __shfl_xor_sync(0xffffffffu, m0, 2)); m1 = fmaxf(m1, __shfl_xor_sync(0xffffffffu, m1, 2));
            const uint32_t off = (uint32_t)(((t & 1) * 8 + g) * 16 + r * 8 + warp) * 4;
            const float mv = (t & 1) ? m1 : m0;
            if (t & 2) asm volatile("st.async.shared::cluster.mbarrier::complete_tx::bytes.f32 [%0], %1, [%2];"
                                    :: "r"(peer + SM_MX + off), "f"(mv), "r"(peer + SM_BAR + BAR_MX) : "memory");
            else asm volatile("st.shared.f32 [%0], %1;" :: "r"(sb + SM_MX + off), "f"(mv) : "memory");
            __syncwarp();
            if (lane == 0) mbar_arrive(bars + BAR_MX);
            mbar_wait_cluster(bars + BAR_MX, 0);
            if (tid < 128) g_q[pair * 256 + r * 128 + tid] = make_uint4(0u, 0u, 0u, 0u);
            const float4* mx = reinterpret_cast<const float4*>(smem + SM_MX);
            const float4 u0 = mx[g * 4 + t], u1 = mx[(g + 8) * 4 + t];
            m0 = fmaxf(fmaxf(u0.x, u0.y), fmaxf(u0.z, u0.w));
            m1 = fmaxf(fmaxf(u1.x, u1.y), fmaxf(u1.z, u1.w));
            m0 = fmaxf(m0, __shfl_xor_sync(0xffffffffu, m0, 1)); m1 = fmaxf(m1, __shfl_xor_sync(0xffffffffu, m1, 1));
            m0 = fmaxf(m0, __shfl_xor_sync(0xffffffffu, m0, 2)); m1 = fmaxf(m1, __shfl_xor_sync(0xffffffffu, m1, 2));
            const float c = 1.4426950408889634f;
            float l0 = 0.f, l1 = 0.f;
            const uint32_t poff = SM_A + (r * 8 + warp) * 4096 + lane * 16;
#pragma unroll
            for (int u = 0; u < 8; u++) {
                float p[8];
#pragma unroll
                for (int i = 0; i < 8; i++) {
                    const uint32_t d = S[2 * u + (i >> 2)][(i >> 1) & 1];
                    p[i] = ex2((((i & 1) ? bf16_hi(d) : bf16_lo(d)) - ((i & 2) ? m1 : m0)) * c);
                }
                l0 += (p[0] + p[1]) + (p[4] + p[5]);
                l1 += (p[2] + p[3]) + (p[6] + p[7]);
                sts128(sb + poff + u * 512, make_uint4(pack_bf16(p[0], p[1]), pack_bf16(p[2], p[3]), pack_bf16(p[4], p[5]), pack_bf16(p[6], p[7])));
            }
            asm volatile("fence.proxy.async.shared::cta;" ::: "memory");
            __syncwarp();
            if (lane == 0)
                asm volatile("cp.async.bulk.shared::cluster.shared::cta.mbarrier::complete_tx::bytes [%0], [%1], %2, [%3];"
                             :: "r"(peer + poff), "r"(sb + poff), "r"(4096), "r"(peer + SM_BAR + BAR_P) : "memory");
            l0 += __shfl_xor_sync(0xffffffffu, l0, 1); l1 += __shfl_xor_sync(0xffffffffu, l1, 1);
            l0 += __shfl_xor_sync(0xffffffffu, l0, 2); l1 += __shfl_xor_sync(0xffffffffu, l1, 2);
            const float lv = (t & 1) ? l1 : l0;
            if (t & 2) asm volatile("st.async.shared::cluster.mbarrier::complete_tx::bytes.f32 [%0], %1, [%2];"
                                    :: "r"(peer + SM_LS + off), "f"(lv), "r"(peer + SM_BAR + BAR_P) : "memory");
            else asm volatile("st.shared.f32 [%0], %1;" :: "r"(sb + SM_LS + off), "f"(lv) : "memory");
            __syncwarp();
            if (lane == 0) mbar_arrive(bars + BAR_P);
            mbar_wait_cluster(bars + BAR_P, 0);
            const float4* ls = reinterpret_cast<const float4*>(smem + SM_LS);
            const float4 v0 = ls[g * 4 + t], v1 = ls[(g + 8) * 4 + t];
            l0 = (v0.x + v0.y) + (v0.z + v0.w);
            l1 = (v1.x + v1.y) + (v1.z + v1.w);
            l0 += __shfl_xor_sync(0xffffffffu, l0, 1); l1 += __shfl_xor_sync(0xffffffffu, l1, 1);
            l0 += __shfl_xor_sync(0xffffffffu, l0, 2); l1 += __shfl_xor_sync(0xffffffffu, l1, 2);
            inv0 = 1.f / l0; inv1 = 1.f / l1;
        }

        const int mp = warp & 1, nt = warp >> 1;
        const int po = nt * 256 + (lane >> 4) * 32 + mp * 16 + (lane & 15);
        uint32_t o_dst_off = offsetof(Scratch, o) + 8 * ((((ki * 4 + (b >> 1)) * 8 + warp) * 32 + ((b & 1) * 4 + (g & 3)) * 4 + t) * 2 + (g >> 2));
        uint32_t o_src_off = offsetof(Scratch, o) + 16 * (ki * 1024 + po);
        uint32_t p_dst_off = offsetof(Scratch, part) + 16 * ((((b * 16 + t) * 4 + (warp & 3)) * 16 + ki) * 8 + g);
        unsigned char* const sc = reinterpret_cast<unsigned char*>(scr);
        uint32_t os_st = sb + tile_slot(O_TILE) * STAGE_BYTES + po * 16;
        uint32_t os_ld = sb + tile_slot(O_TILE) * STAGE_BYTES + lane * 16;
        uint32_t wa0 = sb + (mi >> 1) * 4096 + r8 * 128 + ((((warp & 3) * 2 + (mi & 1)) ^ r8) << 4);
        uint32_t va = sb + ((mi & 1) * 64 + (mi >> 1) * 8 + r8) * 128 + ((warp ^ r8) << 4);
        uint32_t pa = sb + SM_A + lane * 16;
        uint32_t tb = bars;
        asm volatile("" : "+r"(o_dst_off), "+r"(o_src_off), "+r"(p_dst_off));
        asm volatile("" : "+r"(os_st), "+r"(os_ld), "+r"(wa0), "+r"(va), "+r"(pa), "+r"(tb));

        float oa[4][4];
#pragma unroll
        for (int i = 0; i < 4; i++) { oa[i][0] = oa[i][1] = oa[i][2] = oa[i][3] = 0.f; }
        auto pv_tile = [&](int v, int s, uint32_t ph) {
            uint4 p[8];
#pragma unroll
            for (int j = 0; j < 8; j++) p[j] = lds128(pa + ((v >> 3) * 64 + (v & 7)) * 512 + j * 4096);
            const uint32_t vs = va + s * STAGE_BYTES;
            mbar_wait(tb + BAR_FULL + 8 * s, ph);
#pragma unroll
            for (int j2 = 0; j2 < 4; j2++) {
                uint32_t vf[4];
                ldsm4t(vf, vs + j2 * 2048);
                mma16816(oa[(2 * j2) & 3], p[2 * j2].x, p[2 * j2].y, p[2 * j2].z, p[2 * j2].w, vf[0], vf[1]);
                mma16816(oa[(2 * j2 + 1) & 3], p[2 * j2 + 1].x, p[2 * j2 + 1].y, p[2 * j2 + 1].z, p[2 * j2 + 1].w, vf[2], vf[3]);
            }
        };
        {
            int s = tile_slot(16);
            uint32_t ph = tile_par(16);
#pragma unroll 1
            for (int v = 0; v < 15; v++) {
                pv_tile(v, s, ph);
                __syncwarp();
                if (lane == 0) mbar_arrive(tb + BAR_EMPTY + 8 * s);
                if (++s == NSTAGE) { s = 0; ph ^= 1; }
            }
        }
        mbar_wait(tb + BAR_OK, 0);
        mbar_wait(tb + BAR_EMPTY + 8 * tile_slot(O_TILE), tile_par(O_TILE));
        pv_tile(15, tile_slot(31), tile_par(31));
        {
            const float o0 = ((oa[0][0] + oa[1][0]) + (oa[2][0] + oa[3][0])) * inv0;
            const float o1 = ((oa[0][1] + oa[1][1]) + (oa[2][1] + oa[3][1])) * inv0;
            const float o2 = ((oa[0][2] + oa[1][2]) + (oa[2][2] + oa[3][2])) * inv1;
            const float o3 = ((oa[0][3] + oa[1][3]) + (oa[2][3] + oa[3][3])) * inv1;
            asm volatile("red.relaxed.gpu.global.or.b64 [%0], %1;"
                         :: "l"(sc + o_dst_off), "l"((uint64_t)nz(pack_bf16(o0, o1)) | (uint64_t)nz(pack_bf16(o2, o3)) << 32) : "memory");
        }

        {
            spin_clocks(clock64(), O_DELAY);
            const uint4* o_src = reinterpret_cast<const uint4*>(sc + o_src_off);
            uint4 og[4];
#pragma unroll
            for (int j = 0; j < 4; j++) og[j] = ld_relaxed_v4(o_src + j * 64);
            const uint32_t ob = tb + BAR_O + 8 * nt;
            bool done = false;
            int it = 0;
            auto poll = [&]() {
                bool ok = true;
#pragma unroll
                for (int j = 0; j < 4; j++) {
                    if (!valid4(og[j])) { og[j] = ld_relaxed_v4(o_src + j * 64); ok = false; }
                }
                if (__all_sync(0xffffffffu, ok)) {
#pragma unroll
                    for (int j = 0; j < 4; j++) sts128(os_st + j * 1024, og[j]);
                    __syncwarp();
                    if (lane == 0) mbar_arrive(ob);
                    done = true;
                }
            };
            uint32_t wf[4][4][4];
            auto load_wo = [&](int qd) {
#pragma unroll
                for (int k = 0; k < 4; k++)
                    ldsm4t(wf[qd][k], wa0 + tile_slot(32 + (qd >> 1)) * STAGE_BYTES + (qd & 1) * 8192 + (k & 1) * 2048 + (k >> 1) * 1024);
            };
            bool have[4];
#pragma unroll
            for (int qd = 0; qd < 4; qd++) {
                while (true) {
                    have[qd] = mbar_test(tb + BAR_WO + 8 * qd, 0);
                    if (have[qd]) break;
                    if (!done) poll();
                    else if (mbar_test(ob, 0)) break;
                    if (++it > SPIN_LIMIT) give_up();
                }
                if (have[qd]) load_wo(qd);
            }
            while (!done) {
                poll();
                if (++it > SPIN_LIMIT) give_up();
            }
            int rt = nt;
            while (!mbar_test(tb + BAR_O + 8 * rt, 0)) {
                rt ^= 1;
                if (++it > SPIN_LIMIT) give_up();
            }
            auto row_tile = [&](bool first) {
                uint4 of[8];
#pragma unroll
                for (int w = 0; w < 8; w++) of[w] = lds128(os_ld + rt * 4096 + w * 512);
                float acc[4][4];
#pragma unroll
                for (int i = 0; i < 16; i++) acc[i >> 2][i & 3] = 0.f;
#pragma unroll
                for (int qd = 0; qd < 4; qd++) {
                    if (first && !have[qd]) {
                        mbar_wait(tb + BAR_WO + 8 * qd, 0);
                        load_wo(qd);
                    }
#pragma unroll
                    for (int k = 0; k < 4; k++) {
                        const uint4& o4 = of[qd * 2 + (k >> 1)];
                        mma16816(acc[k], wf[qd][k][0], wf[qd][k][1], wf[qd][k][2], wf[qd][k][3], (k & 1) ? o4.z : o4.x, (k & 1) ? o4.w : o4.y);
                    }
                }
                uint32_t w[4];
#pragma unroll
                for (int i = 0; i < 4; i++) w[i] = nz(__float_as_uint((acc[0][i] + acc[1][i]) + (acc[2][i] + acc[3][i])));
                st_relaxed_v4(sc + p_dst_off + rt * 32768, w);
            };
            row_tile(true);
            rt ^= 1;
            mbar_wait(tb + BAR_O + 8 * rt, 0);
            row_tile(false);
        }

        {
            const long long t0 = clock64();
            const uint4* p_src = &g_part[(((b * 16 + ki) * 4 + nt) * 16 + g) * 8 + mp * 4 + t];
            __nv_bfloat16* out_dst = out + (2 * ki + (g & 1)) * 512 + b * 64 + nt * 16 + mp * 4 + t + (g & 2) * 4;
            asm volatile("" : "+l"(p_src), "+l"(out_dst));
            spin_clocks(t0, PART_DELAY);
            uint4 u0 = ld_relaxed_v4(p_src), u1 = ld_relaxed_v4(p_src + 64);
            int it = 0;
            while (true) {
                bool ok = true;
                if (!valid4(u0)) { u0 = ld_relaxed_v4(p_src); ok = false; }
                if (!valid4(u1)) { u1 = ld_relaxed_v4(p_src + 64); ok = false; }
                if (__all_sync(0xffffffffu, ok)) break;
                if (++it > SPIN_LIMIT) give_up();
            }
            float v0 = __uint_as_float(u0.x) + __uint_as_float(u1.x);
            float v1 = __uint_as_float(u0.y) + __uint_as_float(u1.y);
            float v2 = __uint_as_float(u0.z) + __uint_as_float(u1.z);
            float v3 = __uint_as_float(u0.w) + __uint_as_float(u1.w);
#pragma unroll
            for (int d = 4; d < 32; d <<= 1) {
                v0 += __shfl_xor_sync(0xffffffffu, v0, d);
                v1 += __shfl_xor_sync(0xffffffffu, v1, d);
                v2 += __shfl_xor_sync(0xffffffffu, v2, d);
                v3 += __shfl_xor_sync(0xffffffffu, v3, d);
            }
            if (lane < 16) *out_dst = __float2bfloat16_rn((g & 2) ? ((g & 1) ? v3 : v2) : ((g & 1) ? v1 : v0));
        }
    }
}

typedef CUresult (*EncodeTiledFn)(CUtensorMap*, CUtensorMapDataType, cuuint32_t, void*, const cuuint64_t*, const cuuint64_t*,
                                  const cuuint32_t*, const cuuint32_t*, CUtensorMapInterleave, CUtensorMapSwizzle,
                                  CUtensorMapL2promotion, CUtensorMapFloatOOBfill);

void encode3d(EncodeTiledFn enc, CUtensorMap* tm, const void* base, cuuint64_t d0, cuuint64_t d1, cuuint64_t d2,
              cuuint64_t s1, cuuint64_t s2, cuuint32_t b0, cuuint32_t b1, cuuint32_t b2,
              CUtensorMapSwizzle sw = CU_TENSOR_MAP_SWIZZLE_128B) {
    const cuuint64_t dims[3] = {d0, d1, d2};
    const cuuint64_t strides[2] = {s1, s2};
    const cuuint32_t box[3] = {b0, b1, b2};
    const cuuint32_t es[3] = {1, 1, 1};
    enc(tm, CU_TENSOR_MAP_DATA_TYPE_BFLOAT16, 3, const_cast<void*>(base), dims, strides, box, es,
        CU_TENSOR_MAP_INTERLEAVE_NONE, sw, CU_TENSOR_MAP_L2_PROMOTION_L2_256B, CU_TENSOR_MAP_FLOAT_OOB_FILL_NONE);
}

}

extern "C" void kernel_launch(void* const* d_in, const int* in_sizes, int n_in, void* d_out, int out_size) {
    (void)in_sizes; (void)n_in; (void)out_size;
    const __nv_bfloat16* x = (const __nv_bfloat16*)d_in[0];
    const __nv_bfloat16* kc = (const __nv_bfloat16*)d_in[1];
    const __nv_bfloat16* vc = (const __nv_bfloat16*)d_in[2];
    const __nv_bfloat16* wq = (const __nv_bfloat16*)d_in[3];
    const __nv_bfloat16* wo = (const __nv_bfloat16*)d_in[4];

    static EncodeTiledFn enc = nullptr;
    static Scratch* scr = nullptr;
    if (!enc) {
        cudaGetSymbolAddress((void**)&scr, g_scratch);
        void* fn = nullptr;
        cudaDriverEntryPointQueryResult st;
        cudaGetDriverEntryPoint("cuTensorMapEncodeTiled", &fn, cudaEnableDefault, &st);
        enc = (EncodeTiledFn)fn;
        cudaFuncSetAttribute(gqa_fused_kernel, cudaFuncAttributeMaxDynamicSharedMemorySize, SM_TOTAL);
    }
    CUtensorMap tmK, tmV, tmWo, tmWq, tmX;
    encode3d(enc, &tmK, kc, 64, 131072, 2, 256, 128, 64, 64, 2);
    encode3d(enc, &tmV, vc, 64, 131072, 2, 256, 128, 64, 128, 1);
    encode3d(enc, &tmWo, wo, 512, 128, 32, 1024, 131072, 64, 16, 2);
    encode3d(enc, &tmWq, wq, 4096, 256, 2, 8192, 256 * 8192, 32, 256, 2, CU_TENSOR_MAP_SWIZZLE_64B);
    encode3d(enc, &tmX, x, 64, 32, 8, 1024, 128, 64, 32, 8);
    gqa_fused_kernel<<<128, NTHREADS, SM_TOTAL, cudaStreamPerThread>>>(wq, x, (__nv_bfloat16*)d_out, scr, tmK, tmV, tmWo, tmWq, tmX);
}
```

```cpp
#include <cuda_runtime.h>
#include <cuda.h>
#include <cuda_bf16.h>
#include <stdint.h>
#include <stddef.h>

namespace {

constexpr int NSTAGE = 10;
constexpr int STAGE_BYTES = 16384;
constexpr int NTHREADS = 384;

constexpr int W0 = 2;
constexpr uint32_t T_FIRST = 1500;
constexpr uint32_t T_TILE = 640;
constexpr int WINDOW = 8;
constexpr uint32_t T_WO = 21830;
constexpr uint32_t T_WO_PIECE = 350;
constexpr int Q_DELAY = 4000;
constexpr int O_DELAY = 300;
constexpr int PART_DELAY = 300;

constexpr int SM_A = NSTAGE * STAGE_BYTES;
constexpr int SM_BAR = SM_A + 65536;
constexpr int SM_MX = SM_BAR + 320;
constexpr int SM_LS = SM_MX + 1024;
constexpr int SM_TOTAL = SM_LS + 1024;

constexpr int BAR_FULL = 0;
constexpr int BAR_EMPTY = BAR_FULL + 8 * 13;
constexpr int BAR_WO = BAR_EMPTY + 8 * NSTAGE;
constexpr int BAR_MX = BAR_WO + 32;
constexpr int BAR_P = BAR_MX + 8;
constexpr int BAR_OK = BAR_P + 8;
constexpr int BAR_WQ = BAR_OK + 8;
constexpr int BAR_AFREE = BAR_WQ + 8;
constexpr int BAR_O = BAR_AFREE + 8;
constexpr int BAR_END = BAR_O + 32;
static_assert(BAR_END <= 320, "barrier area");

__host__ __device__ constexpr int tile_seq(int n) { return n < 10 ? n : n - 3; }
__host__ __device__ constexpr int tile_slot(int n) { return (n >= 10 && n < 13) ? n : tile_seq(n) % NSTAGE; }
__host__ __device__ constexpr int tile_par(int n) { return (n >= 10 && n < 13) ? 0 : (tile_seq(n) / NSTAGE) & 1; }
constexpr int X_SLOT = 8;
constexpr int O_TILE = 24;

constexpr int SPIN_LIMIT = 1 << 20;

struct Scratch {
    uint4 q[64 * 16 * 16];
    uint4 o[16 * 4 * 8 * 32];
    uint4 part[8 * 16 * 4 * 16 * 8];
    unsigned int cnt[32];
};
__device__ Scratch g_scratch;

__device__ __forceinline__ uint32_t smem_u32(const void* p) { return (uint32_t)__cvta_generic_to_shared(p); }
__device__ __forceinline__ void give_up() {
    asm volatile("st.volatile.global.u32 [%0], %1;\n\texit;" :: "l"(0ull), "r"(0) : "memory");
}
__device__ __forceinline__ uint32_t now_ns() {
    uint32_t t;
    asm volatile("mov.u32 %0, %%globaltimer_lo;" : "=r"(t));
    return t;
}
__device__ __forceinline__ void wait_until(uint32_t due) {
    for (int i = 0; i < (1 << 16) && (int)(now_ns() - due) < 0; i++) {}
}
__device__ __forceinline__ void spin_clocks(long long t0, int n) { while (clock64() - t0 < n) {} }
__device__ __forceinline__ void mbar_init(uint32_t bar, uint32_t count) {
    asm volatile("mbarrier.init.shared::cta.b64 [%0], %1;" :: "r"(bar), "r"(count) : "memory");
}
__device__ __forceinline__ void mbar_expect_tx(uint32_t bar, uint32_t bytes) {
    asm volatile("mbarrier.arrive.expect_tx.shared::cta.b64 _, [%0], %1;" :: "r"(bar), "r"(bytes) : "memory");
}
__device__ __forceinline__ void mbar_arrive(uint32_t bar) {
    asm volatile("mbarrier.arrive.shared::cta.b64 _, [%0];" :: "r"(bar) : "memory");
}
__device__ __forceinline__ void mbar_wait(uint32_t bar, uint32_t parity) {
    uint32_t ok;
    int it = 0;
    do {
        asm volatile("{\n.reg .pred p;\nmbarrier.try_wait.parity.shared::cta.b64 p, [%1], %2;\nselp.u32 %0, 1, 0, p;\n}"
                     : "=r"(ok) : "r"(bar), "r"(parity) : "memory");
        if (++it > SPIN_LIMIT) give_up();
    } while (!ok);
}
__device__ __forceinline__ bool mbar_test(uint32_t bar, uint32_t parity) {
    uint32_t ok;
    asm volatile("{\n.reg .pred p;\nmbarrier.test_wait.parity.shared::cta.b64 p, [%1], %2;\nselp.u32 %0, 1, 0, p;\n}"
                 : "=r"(ok) : "r"(bar), "r"(parity) : "memory");
    return __all_sync(0xffffffffu, ok != 0);
}
__device__ __forceinline__ void mbar_wait_cluster(uint32_t bar, uint32_t parity) {
    uint32_t ok;
    int it = 0;
    do {
        asm volatile("{\n.reg .pred p;\nmbarrier.try_wait.parity.acquire.cluster.shared::cta.b64 p, [%1], %2;\nselp.u32 %0, 1, 0, p;\n}"
                     : "=r"(ok) : "r"(bar), "r"(parity) : "memory");
        if (++it > SPIN_LIMIT) give_up();
    } while (!ok);
}
__device__ __forceinline__ void tma3d(uint32_t dst, const CUtensorMap* tm, int c0, int c1, int c2, uint32_t bar) {
    asm volatile("cp.async.bulk.tensor.3d.shared::cluster.global.mbarrier::complete_tx::bytes [%0], [%1, {%3, %4, %5}], [%2];"
                 :: "r"(dst), "l"(tm), "r"(bar), "r"(c0), "r"(c1), "r"(c2) : "memory");
}
__device__ __forceinline__ void tma3d_hint(uint32_t dst, const CUtensorMap* tm, int c0, int c1, int c2, uint32_t bar, uint64_t pol) {
    asm volatile("cp.async.bulk.tensor.3d.shared::cluster.global.mbarrier::complete_tx::bytes.L2::cache_hint [%0], [%1, {%3, %4, %5}], [%2], %6;"
                 :: "r"(dst), "l"(tm), "r"(bar), "r"(c0), "r"(c1), "r"(c2), "l"(pol) : "memory");
}
__device__ __forceinline__ void ldsm4(uint32_t (&r)[4], uint32_t addr) {
    asm volatile("ldmatrix.sync.aligned.m8n8.x4.shared.b16 {%0, %1, %2, %3}, [%4];"
                 : "=r"(r[0]), "=r"(r[1]), "=r"(r[2]), "=r"(r[3]) : "r"(addr) : "memory");
}
__device__ __forceinline__ void ldsm4t(uint32_t (&r)[4], uint32_t addr) {
    asm volatile("ldmatrix.sync.aligned.m8n8.x4.trans.shared.b16 {%0, %1, %2, %3}, [%4];"
                 : "=r"(r[0]), "=r"(r[1]), "=r"(r[2]), "=r"(r[3]) : "r"(addr) : "memory");
}
__device__ __forceinline__ void mma16816(float (&c)[4], uint32_t a0, uint32_t a1, uint32_t a2, uint32_t a3, uint32_t b0, uint32_t b1) {
    asm volatile("mma.sync.aligned.m16n8k16.row.col.f32.bf16.bf16.f32 {%0, %1, %2, %3}, {%4, %5, %6, %7}, {%8, %9}, {%0, %1, %2, %3};"
                 : "+f"(c[0]), "+f"(c[1]), "+f"(c[2]), "+f"(c[3]) : "r"(a0), "r"(a1), "r"(a2), "r"(a3), "r"(b0), "r"(b1));
}
__device__ __forceinline__ uint32_t pack_bf16(float lo, float hi) {
    uint32_t r;
    asm("cvt.rn.bf16x2.f32 %0, %1, %2;" : "=r"(r) : "f"(hi), "f"(lo));
    return r;
}
__device__ __forceinline__ float bf16_lo(uint32_t d) { return __uint_as_float(d << 16); }
__device__ __forceinline__ float bf16_hi(uint32_t d) { return __uint_as_float(d & 0xffff0000u); }
__device__ __forceinline__ uint32_t max_bf16x2(uint32_t a, uint32_t b) {
    uint32_t r;
    asm("max.bf16x2 %0, %1, %2;" : "=r"(r) : "r"(a), "r"(b));
    return r;
}
__device__ __forceinline__ float ex2(float x) {
    float r;
    asm("ex2.approx.ftz.f32 %0, %1;" : "=f"(r) : "f"(x));
    return r;
}
__device__ __forceinline__ uint4 ld_relaxed_v4(const uint4* p) {
    uint4 v;
    asm volatile("ld.relaxed.gpu.global.v4.u32 {%0, %1, %2, %3}, [%4];" : "=r"(v.x), "=r"(v.y), "=r"(v.z), "=r"(v.w) : "l"(p) : "memory");
    return v;
}
__device__ __forceinline__ void st_relaxed_v4(void* p, const uint32_t (&w)[4]) {
    asm volatile("st.relaxed.gpu.global.v4.u32 [%0], {%1, %2, %3, %4};" :: "l"(p), "r"(w[0]), "r"(w[1]), "r"(w[2]), "r"(w[3]) : "memory");
}
__device__ __forceinline__ uint4 lds128(uint32_t a) {
    uint4 v;
    asm volatile("ld.shared.v4.u32 {%0, %1, %2, %3}, [%4];" : "=r"(v.x), "=r"(v.y), "=r"(v.z), "=r"(v.w) : "r"(a) : "memory");
    return v;
}
__device__ __forceinline__ void sts128(uint32_t a, const uint4& v) {
    asm volatile("st.shared.v4.u32 [%0], {%1, %2, %3, %4};" :: "r"(a), "r"(v.x), "r"(v.y), "r"(v.z), "r"(v.w) : "memory");
}
__device__ __forceinline__ uint32_t nz(uint32_t w) { return w == 0u ? 0x80000000u : w; }
__device__ __forceinline__ bool valid4(const uint4& v) { return v.x != 0u && v.y != 0u && v.z != 0u && v.w != 0u; }
__device__ __forceinline__ void bar_compute() { asm volatile("bar.sync 1, 256;" ::: "memory"); }

__device__ __forceinline__ void arrive_and_wait(unsigned int* cnt, unsigned int n) {
    unsigned int old;
    asm volatile("atom.add.release.gpu.global.u32 %0, [%1], 1;" : "=r"(old) : "l"(cnt) : "memory");
    const unsigned int target = (old | (n - 1)) + 1;
    unsigned int cur;
    int it = 0;
    do {
        asm volatile("ld.acquire.gpu.global.u32 %0, [%1];" : "=r"(cur) : "l"(cnt) : "memory");
        if (++it > SPIN_LIMIT) give_up();
    } while ((int)(cur - target) < 0);
}

__global__ void __cluster_dims__(2, 1, 1) __launch_bounds__(NTHREADS, 1)
gqa_fused_kernel(const __nv_bfloat16* __restrict__ wq, const __nv_bfloat16* __restrict__ x, __nv_bfloat16* __restrict__ out,
                 Scratch* __restrict__ scr,
                 const __grid_constant__ CUtensorMap tmK, const __grid_constant__ CUtensorMap tmV,
                 const __grid_constant__ CUtensorMap tmWo, const __grid_constant__ CUtensorMap tmWq,
                 const __grid_constant__ CUtensorMap tmX) {
    extern __shared__ __align__(1024) unsigned char smem[];
    const int tid = threadIdx.x;
    uint4* const g_q = scr->q;
    uint4* const g_o = scr->o;
    uint4* const g_part = scr->part;
    const uint32_t sb = smem_u32(smem);
    const uint32_t bars = sb + SM_BAR;
    const int warp = tid >> 5, lane = tid & 31;
    const int r = blockIdx.x & 1;
    const int pair = blockIdx.x >> 1;
    const int b = pair >> 3, hkv = pair & 7;
    const int krow = blockIdx.x * 1024;
    uint64_t pol;
    asm volatile("createpolicy.fractional.L2::evict_first.b64 %0, 1.0;" : "=l"(pol));
    const uint32_t t_start = now_ns();

    if (tid == 0) {
        asm volatile("cp.async.bulk.prefetch.L2.global [%0], %1;" :: "l"(x + blockIdx.x * 128), "r"(256) : "memory");
        asm volatile("cp.async.bulk.prefetch.L2.global [%0], %1;" :: "l"(wq + blockIdx.x * 16384), "r"(32768) : "memory");
        mbar_init(bars + BAR_WQ, 1);
#pragma unroll
        for (int n = 0; n < W0; n++) mbar_init(bars + BAR_FULL + 8 * n, 1);
        asm volatile("fence.proxy.async.shared::cta;" ::: "memory");
        mbar_expect_tx(bars + BAR_WQ, 65536);
        tma3d(sb + X_SLOT * STAGE_BYTES, &tmX, 0, 0, 0, bars + BAR_WQ);
        tma3d(sb + SM_A, &tmWq, hkv * 512 + (b * 2 + r) * 32, 0, 0, bars + BAR_WQ);
#pragma unroll
        for (int n = 0; n < W0; n++) {
            mbar_expect_tx(bars + BAR_FULL + 8 * n, STAGE_BYTES);
            tma3d_hint(sb + n * STAGE_BYTES, &tmK, 0, krow + n * 64, 0, bars + BAR_FULL + 8 * n, pol);
        }
#pragma unroll
        for (int off = 8 * W0; off < BAR_END; off += 8)
            if (off != BAR_WQ)
                mbar_init(bars + off, off < BAR_EMPTY ? 1 : off < BAR_WO ? 8 : off < BAR_MX ? 1 : off < BAR_OK ? 9 : off >= BAR_O ? 2 : 1);
        mbar_expect_tx(bars + BAR_MX, 512);
        mbar_expect_tx(bars + BAR_P, 32768 + 512);
        asm volatile("fence.mbarrier_init.release.cluster;" ::: "memory");
        asm volatile("fence.proxy.async.shared::cta;" ::: "memory");
    }
    __syncwarp();
    asm volatile("barrier.cluster.arrive.relaxed.aligned;" ::: "memory");
    __syncthreads();

    const int ki = hkv * 2 + r;
    if (__shfl_sync(0xffffffffu, tid >> 7, 0) == 2) {
        asm volatile("setmaxnreg.dec.sync.aligned.u32 40;");
        if (warp == 8) {
            if (lane == 0) {
                asm volatile("prefetch.tensormap [%0];" :: "l"(&tmV) : "memory");
                asm volatile("prefetch.tensormap [%0];" :: "l"(&tmWo) : "memory");
                uint32_t due = t_start + T_FIRST;
#pragma unroll 1
                for (int n = W0; n < 32; n++) {
                    wait_until(due);
                    due += T_TILE;
                    if (n >= WINDOW) mbar_wait(bars + BAR_FULL + 8 * tile_slot(n - WINDOW), tile_par(n - WINDOW));
                    const int s = tile_slot(n);
                    if (n == X_SLOT) mbar_wait(bars + BAR_AFREE, 0);
                    if (n >= 13) mbar_wait(bars + BAR_EMPTY + 8 * s, tile_par(n) ^ 1);
                    const uint32_t dst = sb + s * STAGE_BYTES;
                    const uint32_t fb = bars + BAR_FULL + 8 * s;
                    mbar_expect_tx(fb, STAGE_BYTES);
                    if (n < 16) tma3d_hint(dst, &tmK, 0, krow + n * 64, 0, fb, pol);
                    else tma3d_hint(dst, &tmV, 0, pair * 2048 + (n - 16) * 128, r, fb, pol);
                }
                mbar_wait(bars + BAR_EMPTY + 8 * tile_slot(32), tile_par(32) ^ 1);
                mbar_wait(bars + BAR_EMPTY + 8 * tile_slot(33), tile_par(33) ^ 1);
                mbar_wait(bars + BAR_FULL + 8 * tile_slot(27), tile_par(27));
                due = now_ns();
                if ((int)(due - (t_start + T_WO)) < 0) due = t_start + T_WO;
                due += blockIdx.x * T_WO_PIECE / 128;
#pragma unroll
                for (int qd = 0; qd < 4; qd++) {
                    wait_until(due);
                    due += T_WO_PIECE;
                    mbar_expect_tx(bars + BAR_WO + 8 * qd, 8192);
                    tma3d(sb + tile_slot(32 + (qd >> 1)) * STAGE_BYTES + (qd & 1) * 8192, &tmWo,
                          b * 64, r * 64 + qd * 16, hkv * 4, bars + BAR_WO + 8 * qd);
                }
            }
        } else if (warp == 9) {
            mbar_wait(bars + BAR_AFREE, 0);
            const uint4 z = make_uint4(0u, 0u, 0u, 0u);
#pragma unroll 1
            for (int i = 0; i < 4; i++) g_o[(ki * 4 + (b >> 1)) * 256 + (i * 2 + (lane >> 4)) * 32 + (b & 1) * 16 + (lane & 15)] = z;
#pragma unroll 4
            for (int i = 0; i < 16; i++) g_part[(((b * 16 + i) * 4 + (lane >> 3)) * 16 + ki) * 8 + (lane & 7)] = z;
            __syncwarp();
            if (lane == 0) {
                arrive_and_wait(scr->cnt, 128);
                mbar_arrive(bars + BAR_OK);
            }
        }
        __syncwarp();
        asm volatile("barrier.cluster.wait.acquire.aligned;" ::: "memory");
    } else {
        asm volatile("setmaxnreg.inc.sync.aligned.u32 232;");
        const int g = lane >> 2, t = lane & 3;
        const int mi = lane >> 3, r8 = lane & 7;
        mbar_wait(bars + BAR_WQ, 0);

        {
            float acc[4][4];
#pragma unroll
            for (int nt = 0; nt < 4; nt++) { acc[nt][0] = acc[nt][1] = acc[nt][2] = acc[nt][3] = 0.f; }
            const uint32_t wa = sb + SM_A + ((warp >> 1) * 128 + lane) * 64;
            const uint32_t xa = sb + X_SLOT * STAGE_BYTES + (warp >> 1) * 8192 + ((warp & 1) * 16 + (mi & 1) * 8 + r8) * 128;
#pragma unroll
            for (int i = 0; i < 4; i++) {
                uint32_t a0[4], a1[4];
                ldsm4(a0, xa + (i >> 1) * 4096 + ((((i & 1) * 4 + (mi >> 1)) ^ r8) << 4));
                ldsm4(a1, xa + (i >> 1) * 4096 + ((((i & 1) * 4 + 2 + (mi >> 1)) ^ r8) << 4));
#pragma unroll
                for (int nt = 0; nt < 4; nt++) {
                    uint32_t bw[4];
                    ldsm4t(bw, wa + i * 2048 + ((nt ^ (r8 >> 1)) << 4));
                    mma16816(acc[nt], a0[0], a0[1], a0[2], a0[3], bw[0], bw[1]);
                    mma16816(acc[nt], a1[0], a1[1], a1[2], a1[3], bw[2], bw[3]);
                }
            }
            float4* red = reinterpret_cast<float4*>(smem + SM_A + 32768);
#pragma unroll
            for (int hf = 0; hf < 2; hf++) {
                const int idx = (warp >> 1) * 256 + ((warp & 1) * 16 + hf * 8 + g) * 4 + t;
                red[idx] = make_float4(acc[0][2 * hf], acc[0][2 * hf + 1], acc[1][2 * hf], acc[1][2 * hf + 1]);
                red[idx + 128] = make_float4(acc[2][2 * hf], acc[2][2 * hf + 1], acc[3][2 * hf], acc[3][2 * hf + 1]);
            }
            bar_compute();
            if (tid < 128) {
                uint32_t w[4];
#pragma unroll
                for (int hf = 0; hf < 2; hf++) {
                    const float4 v0 = red[hf * 128 + tid], v1 = red[256 + hf * 128 + tid], v2 = red[512 + hf * 128 + tid], v3 = red[768 + hf * 128 + tid];
                    w[2 * hf] = nz(pack_bf16((v0.x + v1.x) + (v2.x + v3.x), (v0.y + v1.y) + (v2.y + v3.y)));
                    w[2 * hf + 1] = nz(pack_bf16((v0.z + v1.z) + (v2.z + v3.z), (v0.w + v1.w) + (v2.w + v3.w)));
                }
                st_relaxed_v4(&g_q[(((tid >> 4) * 8 + hkv) * 16 + b * 2 + r) * 16 + (tid & 15)], w);
            }
        }
        uint4 qf[8];
        {
            const uint4* qsrc = &g_q[pair * 256 + tid];
            bar_compute();
            if (tid == 0) mbar_arrive(bars + BAR_AFREE);
            spin_clocks(clock64(), Q_DELAY);
            uint4 w = ld_relaxed_v4(qsrc);
            int it = 0;
            while (!valid4(w)) {
                w = ld_relaxed_v4(qsrc);
                if (++it > SPIN_LIMIT) give_up();
            }
            uint4* qs = reinterpret_cast<uint4*>(smem + SM_A + 49152);
            qs[tid] = w;
            bar_compute();
#pragma unroll
            for (int i = 0; i < 8; i++) qf[i] = qs[((g >> 2) * 4 + (i & 1) * 8 + (i >> 1)) * 16 + (g & 3) * 4 + t];
        }

        uint32_t S[16][2];
        {
            const uint32_t ka = sb + (warp * 8 + r8) * 128;
#pragma unroll
            for (int n = 0; n < 16; n++) {
                const int s = tile_slot(n);
                mbar_wait(bars + BAR_FULL + 8 * s, tile_par(n));
                float e[4] = {0.f, 0.f, 0.f, 0.f}, o[4] = {0.f, 0.f, 0.f, 0.f};
#pragma unroll
                for (int i = 0; i < 4; i++) {
                    uint32_t kf[4];
                    ldsm4(kf, ka + s * STAGE_BYTES + (i >> 1) * 8192 + (((((i & 1) << 2) + mi) ^ r8) << 4));
                    mma16816(e, qf[2 * i].x, qf[2 * i + 1].x, qf[2 * i].y, qf[2 * i + 1].y, kf[0], kf[1]);
                    mma16816(o, qf[2 * i].z, qf[2 * i + 1].z, qf[2 * i].w, qf[2 * i + 1].w, kf[2], kf[3]);
                }
#pragma unroll
                for (int i = 0; i < 2; i++) {
                    const uint32_t d = pack_bf16(e[2 * i] + o[2 * i], e[2 * i + 1] + o[2 * i + 1]);
                    S[n][i] = pack_bf16(bf16_lo(d) * 0.08838834764831845f, bf16_hi(d) * 0.08838834764831845f);
                }
                if (s < NSTAGE) {
                    __syncwarp();
                    if (lane == 0) mbar_arrive(bars + BAR_EMPTY + 8 * s);
                }
            }
        }

        asm volatile("barrier.cluster.wait.acquire.aligned;" ::: "memory");
        uint32_t peer;
        asm("mapa.shared::cluster.u32 %0, %1, %2;" : "=r"(peer) : "r"(sb), "r"(r ^ 1));
        float inv0, inv1;
        {
            uint32_t h0 = S[0][0], h1 = S[0][1];
#pragma unroll
            for (int n = 1; n < 16; n++) { h0 = max_bf16x2(h0, S[n][0]); h1 = max_bf16x2(h1, S[n][1]); }
            float m0 = fmaxf(bf16_lo(h0), bf16_hi(h0)), m1 = fmaxf(bf16_lo(h1), bf16_hi(h1));
            m0 = fmaxf(m0, __shfl_xor_sync(0xffffffffu, m0, 1)); m1 = fmaxf(m1, __shfl_xor_sync(0xffffffffu, m1, 1));
            m0 = fmaxf(m0, __shfl_xor_sync(0xffffffffu, m0, 2)); m1 = fmaxf(m1, __shfl_xor_sync(0xffffffffu, m1, 2));
            const uint32_t off = (uint32_t)(((t & 1) * 8 + g) * 16 + r * 8 + warp) * 4;
            const float mv = (t & 1) ? m1 : m0;
            if (t & 2) asm volatile("st.async.shared::cluster.mbarrier::complete_tx::bytes.f32 [%0], %1, [%2];"
                                    :: "r"(peer + SM_MX + off), "f"(mv), "r"(peer + SM_BAR + BAR_MX) : "memory");
            else asm volatile("st.shared.f32 [%0], %1;" :: "r"(sb + SM_MX + off), "f"(mv) : "memory");
            __syncwarp();
            if (lane == 0) mbar_arrive(bars + BAR_MX);
            mbar_wait_cluster(bars + BAR_MX, 0);
            if (tid < 128) g_q[pair * 256 + r * 128 + tid] = make_uint4(0u, 0u, 0u, 0u);
            const float4* mx = reinterpret_cast<const float4*>(smem + SM_MX);
            const float4 u0 = mx[g * 4 + t], u1 = mx[(g + 8) * 4 + t];
            m0 = fmaxf(fmaxf(u0.x, u0.y), fmaxf(u0.z, u0.w));
            m1 = fmaxf(fmaxf(u1.x, u1.y), fmaxf(u1.z, u1.w));
            m0 = fmaxf(m0, __shfl_xor_sync(0xffffffffu, m0, 1)); m1 = fmaxf(m1, __shfl_xor_sync(0xffffffffu, m1, 1));
            m0 = fmaxf(m0, __shfl_xor_sync(0xffffffffu, m0, 2)); m1 = fmaxf(m1, __shfl_xor_sync(0xffffffffu, m1, 2));
            const float c = 1.4426950408889634f;
            float l0 = 0.f, l1 = 0.f;
            const uint32_t poff = SM_A + (r * 8 + warp) * 4096 + lane * 16;
#pragma unroll
            for (int u = 0; u < 8; u++) {
                float p[8];
#pragma unroll
                for (int i = 0; i < 8; i++) {
                    const uint32_t d = S[2 * u + (i >> 2)][(i >> 1) & 1];
                    p[i] = ex2((((i & 1) ? bf16_hi(d) : bf16_lo(d)) - ((i & 2) ? m1 : m0)) * c);
                }
                l0 += (p[0] + p[1]) + (p[4] + p[5]);
                l1 += (p[2] + p[3]) + (p[6] + p[7]);
                sts128(sb + poff + u * 512, make_uint4(pack_bf16(p[0], p[1]), pack_bf16(p[2], p[3]), pack_bf16(p[4], p[5]), pack_bf16(p[6], p[7])));
            }
            asm volatile("fence.proxy.async.shared::cta;" ::: "memory");
            __syncwarp();
            if (lane == 0)
                asm volatile("cp.async.bulk.shared::cluster.shared::cta.mbarrier::complete_tx::bytes [%0], [%1], %2, [%3];"
                             :: "r"(peer + poff), "r"(sb + poff), "r"(4096), "r"(peer + SM_BAR + BAR_P) : "memory");
            l0 += __shfl_xor_sync(0xffffffffu, l0, 1); l1 += __shfl_xor_sync(0xffffffffu, l1, 1);
            l0 += __shfl_xor_sync(0xffffffffu, l0, 2); l1 += __shfl_xor_sync(0xffffffffu, l1, 2);
            const float lv = (t & 1) ? l1 : l0;
            if (t & 2) asm volatile("st.async.shared::cluster.mbarrier::complete_tx::bytes.f32 [%0], %1, [%2];"
                                    :: "r"(peer + SM_LS + off), "f"(lv), "r"(peer + SM_BAR + BAR_P) : "memory");
            else asm volatile("st.shared.f32 [%0], %1;" :: "r"(sb + SM_LS + off), "f"(lv) : "memory");
            __syncwarp();
            if (lane == 0) mbar_arrive(bars + BAR_P);
            mbar_wait_cluster(bars + BAR_P, 0);
            const float4* ls = reinterpret_cast<const float4*>(smem + SM_LS);
            const float4 v0 = ls[g * 4 + t], v1 = ls[(g + 8) * 4 + t];
            l0 = (v0.x + v0.y) + (v0.z + v0.w);
            l1 = (v1.x + v1.y) + (v1.z + v1.w);
            l0 += __shfl_xor_sync(0xffffffffu, l0, 1); l1 += __shfl_xor_sync(0xffffffffu, l1, 1);
            l0 += __shfl_xor_sync(0xffffffffu, l0, 2); l1 += __shfl_xor_sync(0xffffffffu, l1, 2);
            inv0 = 1.f / l0; inv1 = 1.f / l1;
        }

        const int mp = warp & 1, nt = warp >> 1;
        const int po = nt * 256 + (lane >> 4) * 32 + mp * 16 + (lane & 15);
        uint32_t o_dst_off = offsetof(Scratch, o) + 8 * ((((ki * 4 + (b >> 1)) * 8 + warp) * 32 + ((b & 1) * 4 + (g & 3)) * 4 + t) * 2 + (g >> 2));
        uint32_t o_src_off = offsetof(Scratch, o) + 16 * (ki * 1024 + po);
        uint32_t p_dst_off = offsetof(Scratch, part) + 16 * ((((b * 16 + t) * 4 + (warp & 3)) * 16 + ki) * 8 + g);
        unsigned char* const sc = reinterpret_cast<unsigned char*>(scr);
        uint32_t os_st = sb + tile_slot(O_TILE) * STAGE_BYTES + po * 16;
        uint32_t os_ld = sb + tile_slot(O_TILE) * STAGE_BYTES + lane * 16;
        uint32_t wa0 = sb + (mi >> 1) * 4096 + r8 * 128 + ((((warp & 3) * 2 + (mi & 1)) ^ r8) << 4);
        uint32_t va = sb + ((mi & 1) * 64 + (mi >> 1) * 8 + r8) * 128 + ((warp ^ r8) << 4);
        uint32_t pa = sb + SM_A + lane * 16;
        uint32_t tb = bars;
        asm volatile("" : "+r"(o_dst_off), "+r"(o_src_off), "+r"(p_dst_off));
        asm volatile("" : "+r"(os_st), "+r"(os_ld), "+r"(wa0), "+r"(va), "+r"(pa), "+r"(tb));

        float oa[4][4];
#pragma unroll
        for (int i = 0; i < 4; i++) { oa[i][0] = oa[i][1] = oa[i][2] = oa[i][3] = 0.f; }
        auto pv_tile = [&](int v, int s, uint32_t ph) {
            uint4 p[8];
#pragma unroll
            for (int j = 0; j < 8; j++) p[j] = lds128(pa + ((v >> 3) * 64 + (v & 7)) * 512 + j * 4096);
            const uint32_t vs = va + s * STAGE_BYTES;
            mbar_wait(tb + BAR_FULL + 8 * s, ph);
#pragma unroll
            for (int j2 = 0; j2 < 4; j2++) {
                uint32_t vf[4];
                ldsm4t(vf, vs + j2 * 2048);
                mma16816(oa[(2 * j2) & 3], p[2 * j2].x, p[2 * j2].y, p[2 * j2].z, p[2 * j2].w, vf[0], vf[1]);
                mma16816(oa[(2 * j2 + 1) & 3], p[2 * j2 + 1].x, p[2 * j2 + 1].y, p[2 * j2 + 1].z, p[2 * j2 + 1].w, vf[2], vf[3]);
            }
        };
        {
            int s = tile_slot(16);
            uint32_t ph = tile_par(16);
#pragma unroll 1
            for (int v = 0; v < 15; v++) {
                pv_tile(v, s, ph);
                __syncwarp();
                if (lane == 0) mbar_arrive(tb + BAR_EMPTY + 8 * s);
                if (++s == NSTAGE) { s = 0; ph ^= 1; }
            }
        }
        mbar_wait(tb + BAR_OK, 0);
        mbar_wait(tb + BAR_EMPTY + 8 * tile_slot(O_TILE), tile_par(O_TILE));
        pv_tile(15, tile_slot(31), tile_par(31));
        {
            const float o0 = ((oa[0][0] + oa[1][0]) + (oa[2][0] + oa[3][0])) * inv0;
            const float o1 = ((oa[0][1] + oa[1][1]) + (oa[2][1] + oa[3][1])) * inv0;
            const float o2 = ((oa[0][2] + oa[1][2]) + (oa[2][2] + oa[3][2])) * inv1;
            const float o3 = ((oa[0][3] + oa[1][3]) + (oa[2][3] + oa[3][3])) * inv1;
            asm volatile("red.relaxed.gpu.global.or.b64 [%0], %1;"
                         :: "l"(sc + o_dst_off), "l"((uint64_t)nz(pack_bf16(o0, o1)) | (uint64_t)nz(pack_bf16(o2, o3)) << 32) : "memory");
        }

        {
            spin_clocks(clock64(), O_DELAY);
            const uint4* o_src = reinterpret_cast<const uint4*>(sc + o_src_off);
            uint4 og[4];
#pragma unroll
            for (int j = 0; j < 4; j++) og[j] = ld_relaxed_v4(o_src + j * 64);
            const uint32_t ob = tb + BAR_O + 8 * nt;
            bool done = false;
            int it = 0;
            auto poll = [&]() {
                bool ok = true;
#pragma unroll
                for (int j = 0; j < 4; j++) {
                    if (!valid4(og[j])) { og[j] = ld_relaxed_v4(o_src + j * 64); ok = false; }
                }
                if (__all_sync(0xffffffffu, ok)) {
#pragma unroll
                    for (int j = 0; j < 4; j++) sts128(os_st + j * 1024, og[j]);
                    __syncwarp();
                    if (lane == 0) mbar_arrive(ob);
                    done = true;
                }
            };
            uint32_t wf[4][4][4];
            auto load_wo = [&](int qd) {
#pragma unroll
                for (int k = 0; k < 4; k++)
                    ldsm4t(wf[qd][k], wa0 + tile_slot(32 + (qd >> 1)) * STAGE_BYTES + (qd & 1) * 8192 + (k & 1) * 2048 + (k >> 1) * 1024);
            };
            bool have[4];
#pragma unroll
            for (int qd = 0; qd < 4; qd++) {
                while (true) {
                    have[qd] = mbar_test(tb + BAR_WO + 8 * qd, 0);
                    if (have[qd]) break;
                    if (!done) poll();
                    else if (mbar_test(ob, 0)) break;
                    if (++it > SPIN_LIMIT) give_up();
                }
                if (have[qd]) load_wo(qd);
            }
            while (!done) {
                poll();
                if (++it > SPIN_LIMIT) give_up();
            }
            int rt = nt;
            while (!mbar_test(tb + BAR_O + 8 * rt, 0)) {
                rt ^= 1;
                if (++it > SPIN_LIMIT) give_up();
            }
            auto row_tile = [&](bool first) {
                uint4 of[8];
#pragma unroll
                for (int w = 0; w < 8; w++) of[w] = lds128(os_ld + rt * 4096 + w * 512);
                float acc[4][4];
#pragma unroll
                for (int i = 0; i < 16; i++) acc[i >> 2][i & 3] = 0.f;
#pragma unroll
                for (int qd = 0; qd < 4; qd++) {
                    if (first && !have[qd]) {
                        mbar_wait(tb + BAR_WO + 8 * qd, 0);
                        load_wo(qd);
                    }
#pragma unroll
                    for (int k = 0; k < 4; k++) {
                        const uint4& o4 = of[qd * 2 + (k >> 1)];
                        mma16816(acc[k], wf[qd][k][0], wf[qd][k][1], wf[qd][k][2], wf[qd][k][3], (k & 1) ? o4.z : o4.x, (k & 1) ? o4.w : o4.y);
                    }
                }
                uint32_t w[4];
#pragma unroll
                for (int i = 0; i < 4; i++) w[i] = nz(__float_as_uint((acc[0][i] + acc[1][i]) + (acc[2][i] + acc[3][i])));
                st_relaxed_v4(sc + p_dst_off + rt * 32768, w);
            };
            row_tile(true);
            rt ^= 1;
            mbar_wait(tb + BAR_O + 8 * rt, 0);
            row_tile(false);
        }

        if (mp == 0) {
            const long long t0 = clock64();
            const uint4* p_src = &g_part[((b * 16 + ki) * 4 + nt) * 128 + lane];
            __nv_bfloat16* out_dst = out + (2 * ki + (mi & 1)) * 512 + b * 64 + nt * 16 + r8 + (mi >> 1) * 8;
            asm volatile("" : "+l"(p_src), "+l"(out_dst));
            spin_clocks(t0, PART_DELAY);
            uint4 u[4];
#pragma unroll
            for (int j = 0; j < 4; j++) u[j] = ld_relaxed_v4(p_src + j * 32);
            int it = 0;
            while (true) {
                bool ok = true;
#pragma unroll
                for (int j = 0; j < 4; j++) {
                    if (!valid4(u[j])) { u[j] = ld_relaxed_v4(p_src + j * 32); ok = false; }
                }
                if (__all_sync(0xffffffffu, ok)) break;
                if (++it > SPIN_LIMIT) give_up();
            }
            float v0 = (__uint_as_float(u[0].x) + __uint_as_float(u[1].x)) + (__uint_as_float(u[2].x) + __uint_as_float(u[3].x));
            float v1 = (__uint_as_float(u[0].y) + __uint_as_float(u[1].y)) + (__uint_as_float(u[2].y) + __uint_as_float(u[3].y));
            float v2 = (__uint_as_float(u[0].z) + __uint_as_float(u[1].z)) + (__uint_as_float(u[2].z) + __uint_as_float(u[3].z));
            float v3 = (__uint_as_float(u[0].w) + __uint_as_float(u[1].w)) + (__uint_as_float(u[2].w) + __uint_as_float(u[3].w));
#pragma unroll
            for (int d = 8; d < 32; d <<= 1) {
                v0 += __shfl_xor_sync(0xffffffffu, v0, d);
                v1 += __shfl_xor_sync(0xffffffffu, v1, d);
                v2 += __shfl_xor_sync(0xffffffffu, v2, d);
                v3 += __shfl_xor_sync(0xffffffffu, v3, d);
            }
            *out_dst = __float2bfloat16_rn((mi & 2) ? ((mi & 1) ? v3 : v2) : ((mi & 1) ? v1 : v0));
        }
    }
}

typedef CUresult (*EncodeTiledFn)(CUtensorMap*, CUtensorMapDataType, cuuint32_t, void*, const cuuint64_t*, const cuuint64_t*,
                                  const cuuint32_t*, const cuuint32_t*, CUtensorMapInterleave, CUtensorMapSwizzle,
                                  CUtensorMapL2promotion, CUtensorMapFloatOOBfill);

void encode3d(EncodeTiledFn enc, CUtensorMap* tm, const void* base, cuuint64_t d0, cuuint64_t d1, cuuint64_t d2,
              cuuint64_t s1, cuuint64_t s2, cuuint32_t b0, cuuint32_t b1, cuuint32_t b2,
              CUtensorMapSwizzle sw = CU_TENSOR_MAP_SWIZZLE_128B,
              CUtensorMapL2promotion promo = CU_TENSOR_MAP_L2_PROMOTION_L2_256B) {
    const cuuint64_t dims[3] = {d0, d1, d2};
    const cuuint64_t strides[2] = {s1, s2};
    const cuuint32_t box[3] = {b0, b1, b2};
    const cuuint32_t es[3] = {1, 1, 1};
    enc(tm, CU_TENSOR_MAP_DATA_TYPE_BFLOAT16, 3, const_cast<void*>(base), dims, strides, box, es,
        CU_TENSOR_MAP_INTERLEAVE_NONE, sw, promo, CU_TENSOR_MAP_FLOAT_OOB_FILL_NONE);
}

}

extern "C" void kernel_launch(void* const* d_in, const int* in_sizes, int n_in, void* d_out, int out_size) {
    (void)in_sizes; (void)n_in; (void)out_size;
    const __nv_bfloat16* x = (const __nv_bfloat16*)d_in[0];
    const __nv_bfloat16* kc = (const __nv_bfloat16*)d_in[1];
    const __nv_bfloat16* vc = (const __nv_bfloat16*)d_in[2];
    const __nv_bfloat16* wq = (const __nv_bfloat16*)d_in[3];
    const __nv_bfloat16* wo = (const __nv_bfloat16*)d_in[4];

    static EncodeTiledFn enc = nullptr;
    static Scratch* scr = nullptr;
    if (!enc) {
        cudaGetSymbolAddress((void**)&scr, g_scratch);
        void* fn = nullptr;
        cudaDriverEntryPointQueryResult st;
        cudaGetDriverEntryPoint("cuTensorMapEncodeTiled", &fn, cudaEnableDefault, &st);
        enc = (EncodeTiledFn)fn;
        cudaFuncSetAttribute(gqa_fused_kernel, cudaFuncAttributeMaxDynamicSharedMemorySize, SM_TOTAL);
    }
    CUtensorMap tmK, tmV, tmWo, tmWq, tmX;
    encode3d(enc, &tmK, kc, 64, 131072, 2, 256, 128, 64, 64, 2);
    encode3d(enc, &tmV, vc, 64, 131072, 2, 256, 128, 64, 128, 1);
    encode3d(enc, &tmWo, wo, 512, 128, 32, 1024, 131072, 64, 16, 4, CU_TENSOR_MAP_SWIZZLE_128B, CU_TENSOR_MAP_L2_PROMOTION_NONE);
    encode3d(enc, &tmWq, wq, 4096, 256, 2, 8192, 256 * 8192, 32, 256, 2, CU_TENSOR_MAP_SWIZZLE_64B);
    encode3d(enc, &tmX, x, 64, 32, 8, 1024, 128, 64, 32, 8);
    gqa_fused_kernel<<<128, NTHREADS, SM_TOTAL, cudaStreamPerThread>>>(wq, x, (__nv_bfloat16*)d_out, scr, tmK, tmV, tmWo, tmWq, tmX);
}
```

```cpp
#include <cuda_runtime.h>
#include <cuda.h>
#include <cuda_bf16.h>
#include <stdint.h>
#include <stddef.h>

namespace {

constexpr int NSTAGE = 10;
constexpr int STAGE_BYTES = 16384;
constexpr int NTHREADS = 384;

constexpr int W0 = 2;
constexpr uint32_t T_FIRST = 1500;
constexpr uint32_t T_TILE = 640;
constexpr int WINDOW = 8;
constexpr uint32_t T_WO = 21830;
constexpr uint32_t T_WO_PIECE = 350;
constexpr int Q_DELAY = 4000;
constexpr int O_DELAY = 300;
constexpr int PART_DELAY = 300;

constexpr int SM_A = NSTAGE * STAGE_BYTES;
constexpr int SM_BAR = SM_A + 65536;
constexpr int SM_MX = SM_BAR + 320;
constexpr int SM_LS = SM_MX + 1024;
constexpr int SM_TOTAL = SM_LS + 1024;

constexpr int BAR_FULL = 0;
constexpr int BAR_EMPTY = BAR_FULL + 8 * 13;
constexpr int BAR_WO = BAR_EMPTY + 8 * NSTAGE;
constexpr int BAR_MX = BAR_WO + 32;
constexpr int BAR_P = BAR_MX + 8;
constexpr int BAR_OK = BAR_P + 8;
constexpr int BAR_WQ = BAR_OK + 8;
constexpr int BAR_AFREE = BAR_WQ + 8;
constexpr int BAR_O = BAR_AFREE + 8;
constexpr int BAR_END = BAR_O + 32;
static_assert(BAR_END <= 320, "barrier area");

__host__ __device__ constexpr int tile_seq(int n) { return n < 10 ? n : n - 3; }
__host__ __device__ constexpr int tile_slot(int n) { return (n >= 10 && n < 13) ? n : tile_seq(n) % NSTAGE; }
__host__ __device__ constexpr int tile_par(int n) { return (n >= 10 && n < 13) ? 0 : (tile_seq(n) / NSTAGE) & 1; }
constexpr int X_SLOT = 8;
constexpr int O_TILE = 24;

constexpr int SPIN_LIMIT = 1 << 20;

struct Scratch {
    uint4 q[64 * 16 * 16];
    uint4 o[16 * 4 * 8 * 32];
    uint4 part[8 * 16 * 4 * 16 * 8];
    unsigned int cnt[32];
};
__device__ Scratch g_scratch;

__device__ __forceinline__ uint32_t smem_u32(const void* p) { return (uint32_t)__cvta_generic_to_shared(p); }
__device__ __forceinline__ void give_up() {
    asm volatile("st.volatile.global.u32 [%0], %1;\n\texit;" :: "l"(0ull), "r"(0) : "memory");
}
__device__ __forceinline__ uint32_t now_ns() {
    uint32_t t;
    asm volatile("mov.u32 %0, %%globaltimer_lo;" : "=r"(t));
    return t;
}
__device__ __forceinline__ void wait_until(uint32_t due) {
    for (int i = 0; i < (1 << 16) && (int)(now_ns() - due) < 0; i++) {}
}
__device__ __forceinline__ void spin_clocks(long long t0, int n) { while (clock64() - t0 < n) {} }
__device__ __forceinline__ void mbar_init(uint32_t bar, uint32_t count) {
    asm volatile("mbarrier.init.shared::cta.b64 [%0], %1;" :: "r"(bar), "r"(count) : "memory");
}
__device__ __forceinline__ void mbar_expect_tx(uint32_t bar, uint32_t bytes) {
    asm volatile("mbarrier.arrive.expect_tx.shared::cta.b64 _, [%0], %1;" :: "r"(bar), "r"(bytes) : "memory");
}
__device__ __forceinline__ void mbar_arrive(uint32_t bar) {
    asm volatile("mbarrier.arrive.shared::cta.b64 _, [%0];" :: "r"(bar) : "memory");
}
__device__ __forceinline__ void mbar_wait(uint32_t bar, uint32_t parity) {
    uint32_t ok;
    int it = 0;
    do {
        asm volatile("{\n.reg .pred p;\nmbarrier.try_wait.parity.shared::cta.b64 p, [%1], %2;\nselp.u32 %0, 1, 0, p;\n}"
                     : "=r"(ok) : "r"(bar), "r"(parity) : "memory");
        if (++it > SPIN_LIMIT) give_up();
    } while (!ok);
}
__device__ __forceinline__ bool mbar_test(uint32_t bar, uint32_t parity) {
    uint32_t ok;
    asm volatile("{\n.reg .pred p;\nmbarrier.test_wait.parity.shared::cta.b64 p, [%1], %2;\nselp.u32 %0, 1, 0, p;\n}"
                 : "=r"(ok) : "r"(bar), "r"(parity) : "memory");
    return __all_sync(0xffffffffu, ok != 0);
}
__device__ __forceinline__ void mbar_wait_cluster(uint32_t bar, uint32_t parity) {
    uint32_t ok;
    int it = 0;
    do {
        asm volatile("{\n.reg .pred p;\nmbarrier.try_wait.parity.acquire.cluster.shared::cta.b64 p, [%1], %2;\nselp.u32 %0, 1, 0, p;\n}"
                     : "=r"(ok) : "r"(bar), "r"(parity) : "memory");
        if (++it > SPIN_LIMIT) give_up();
    } while (!ok);
}
__device__ __forceinline__ void tma3d(uint32_t dst, const CUtensorMap* tm, int c0, int c1, int c2, uint32_t bar) {
    asm volatile("cp.async.bulk.tensor.3d.shared::cluster.global.mbarrier::complete_tx::bytes [%0], [%1, {%3, %4, %5}], [%2];"
                 :: "r"(dst), "l"(tm), "r"(bar), "r"(c0), "r"(c1), "r"(c2) : "memory");
}
__device__ __forceinline__ void tma3d_hint(uint32_t dst, const CUtensorMap* tm, int c0, int c1, int c2, uint32_t bar, uint64_t pol) {
    asm volatile("cp.async.bulk.tensor.3d.shared::cluster.global.mbarrier::complete_tx::bytes.L2::cache_hint [%0], [%1, {%3, %4, %5}], [%2], %6;"
                 :: "r"(dst), "l"(tm), "r"(bar), "r"(c0), "r"(c1), "r"(c2), "l"(pol) : "memory");
}
__device__ __forceinline__ void ldsm4(uint32_t (&r)[4], uint32_t addr) {
    asm volatile("ldmatrix.sync.aligned.m8n8.x4.shared.b16 {%0, %1, %2, %3}, [%4];"
                 : "=r"(r[0]), "=r"(r[1]), "=r"(r[2]), "=r"(r[3]) : "r"(addr) : "memory");
}
__device__ __forceinline__ void ldsm4t(uint32_t (&r)[4], uint32_t addr) {
    asm volatile("ldmatrix.sync.aligned.m8n8.x4.trans.shared.b16 {%0, %1, %2, %3}, [%4];"
                 : "=r"(r[0]), "=r"(r[1]), "=r"(r[2]), "=r"(r[3]) : "r"(addr) : "memory");
}
__device__ __forceinline__ void mma16816(float (&c)[4], uint32_t a0, uint32_t a1, uint32_t a2, uint32_t a3, uint32_t b0, uint32_t b1) {
    asm volatile("mma.sync.aligned.m16n8k16.row.col.f32.bf16.bf16.f32 {%0, %1, %2, %3}, {%4, %5, %6, %7}, {%8, %9}, {%0, %1, %2, %3};"
                 : "+f"(c[0]), "+f"(c[1]), "+f"(c[2]), "+f"(c[3]) : "r"(a0), "r"(a1), "r"(a2), "r"(a3), "r"(b0), "r"(b1));
}
__device__ __forceinline__ uint32_t pack_bf16(float lo, float hi) {
    uint32_t r;
    asm("cvt.rn.bf16x2.f32 %0, %1, %2;" : "=r"(r) : "f"(hi), "f"(lo));
    return r;
}
__device__ __forceinline__ float bf16_lo(uint32_t d) { return __uint_as_float(d << 16); }
__device__ __forceinline__ float bf16_hi(uint32_t d) { return __uint_as_float(d & 0xffff0000u); }
__device__ __forceinline__ uint32_t max_bf16x2(uint32_t a, uint32_t b) {
    uint32_t r;
    asm("max.bf16x2 %0, %1, %2;" : "=r"(r) : "r"(a), "r"(b));
    return r;
}
__device__ __forceinline__ float ex2(float x) {
    float r;
    asm("ex2.approx.ftz.f32 %0, %1;" : "=f"(r) : "f"(x));
    return r;
}
__device__ __forceinline__ uint4 ld_relaxed_v4(const uint4* p) {
    uint4 v;
    asm volatile("ld.relaxed.gpu.global.v4.u32 {%0, %1, %2, %3}, [%4];" : "=r"(v.x), "=r"(v.y), "=r"(v.z), "=r"(v.w) : "l"(p) : "memory");
    return v;
}
__device__ __forceinline__ void st_relaxed_v4(void* p, const uint32_t (&w)[4]) {
    asm volatile("st.relaxed.gpu.global.v4.u32 [%0], {%1, %2, %3, %4};" :: "l"(p), "r"(w[0]), "r"(w[1]), "r"(w[2]), "r"(w[3]) : "memory");
}
__device__ __forceinline__ uint4 lds128(uint32_t a) {
    uint4 v;
    asm volatile("ld.shared.v4.u32 {%0, %1, %2, %3}, [%4];" : "=r"(v.x), "=r"(v.y), "=r"(v.z), "=r"(v.w) : "r"(a) : "memory");
    return v;
}
__device__ __forceinline__ void sts128(uint32_t a, const uint4& v) {
    asm volatile("st.shared.v4.u32 [%0], {%1, %2, %3, %4};" :: "r"(a), "r"(v.x), "r"(v.y), "r"(v.z), "r"(v.w) : "memory");
}
__device__ __forceinline__ uint32_t nz(uint32_t w) { return w == 0u ? 0x80000000u : w; }
__device__ __forceinline__ bool valid4(const uint4& v) { return v.x != 0u && v.y != 0u && v.z != 0u && v.w != 0u; }
__device__ __forceinline__ void bar_compute() { asm volatile("bar.sync 1, 256;" ::: "memory"); }

__device__ __forceinline__ void arrive_and_wait(unsigned int* cnt, unsigned int n) {
    unsigned int old;
    asm volatile("atom.add.release.gpu.global.u32 %0, [%1], 1;" : "=r"(old) : "l"(cnt) : "memory");
    const unsigned int target = (old | (n - 1)) + 1;
    unsigned int cur;
    int it = 0;
    do {
        asm volatile("ld.acquire.gpu.global.u32 %0, [%1];" : "=r"(cur) : "l"(cnt) : "memory");
        if (++it > SPIN_LIMIT) give_up();
    } while ((int)(cur - target) < 0);
}

__global__ void __cluster_dims__(2, 1, 1) __launch_bounds__(NTHREADS, 1)
gqa_fused_kernel(const __nv_bfloat16* __restrict__ wq, const __nv_bfloat16* __restrict__ x, __nv_bfloat16* __restrict__ out,
                 Scratch* __restrict__ scr,
                 const __grid_constant__ CUtensorMap tmK, const __grid_constant__ CUtensorMap tmV,
                 const __grid_constant__ CUtensorMap tmWo, const __grid_constant__ CUtensorMap tmWq,
                 const __grid_constant__ CUtensorMap tmX) {
    extern __shared__ __align__(1024) unsigned char smem[];
    const int tid = threadIdx.x;
    uint4* const g_q = scr->q;
    uint4* const g_o = scr->o;
    uint4* const g_part = scr->part;
    const uint32_t sb = smem_u32(smem);
    const uint32_t bars = sb + SM_BAR;
    const int warp = tid >> 5, lane = tid & 31;
    const int r = blockIdx.x & 1;
    const int pair = blockIdx.x >> 1;
    const int b = pair >> 3, hkv = pair & 7;
    const int krow = blockIdx.x * 1024;
    uint64_t pol;
    asm volatile("createpolicy.fractional.L2::evict_first.b64 %0, 1.0;" : "=l"(pol));
    const uint32_t t_start = now_ns();

    if (tid == 0) {
        asm volatile("cp.async.bulk.prefetch.L2.global [%0], %1;" :: "l"(x + blockIdx.x * 128), "r"(256) : "memory");
        asm volatile("cp.async.bulk.prefetch.L2.global [%0], %1;" :: "l"(wq + blockIdx.x * 16384), "r"(32768) : "memory");
        mbar_init(bars + BAR_WQ, 1);
#pragma unroll
        for (int n = 0; n < W0; n++) mbar_init(bars + BAR_FULL + 8 * n, 1);
        asm volatile("fence.proxy.async.shared::cta;" ::: "memory");
        mbar_expect_tx(bars + BAR_WQ, 65536);
        tma3d(sb + X_SLOT * STAGE_BYTES, &tmX, 0, 0, 0, bars + BAR_WQ);
        tma3d(sb + SM_A, &tmWq, hkv * 512 + (b * 2 + r) * 32, 0, 0, bars + BAR_WQ);
#pragma unroll
        for (int n = 0; n < W0; n++) {
            mbar_expect_tx(bars + BAR_FULL + 8 * n, STAGE_BYTES);
            tma3d_hint(sb + n * STAGE_BYTES, &tmK, 0, krow + n * 64, 0, bars + BAR_FULL + 8 * n, pol);
        }
#pragma unroll
        for (int off = 8 * W0; off < BAR_END; off += 8)
            if (off != BAR_WQ)
                mbar_init(bars + off, off < BAR_EMPTY ? 1 : off < BAR_WO ? 8 : off < BAR_MX ? 1 : off < BAR_OK ? 9 : off >= BAR_O ? 2 : 1);
        mbar_expect_tx(bars + BAR_MX, 512);
        mbar_expect_tx(bars + BAR_P, 32768 + 512);
        asm volatile("fence.mbarrier_init.release.cluster;" ::: "memory");
        asm volatile("fence.proxy.async.shared::cta;" ::: "memory");
    }
    __syncwarp();
    asm volatile("barrier.cluster.arrive.relaxed.aligned;" ::: "memory");
    __syncthreads();

    const int ki = hkv * 2 + r;
    if (__shfl_sync(0xffffffffu, tid >> 7, 0) == 2) {
        asm volatile("setmaxnreg.dec.sync.aligned.u32 40;");
        if (warp == 8) {
            if (lane == 0) {
                asm volatile("prefetch.tensormap [%0];" :: "l"(&tmV) : "memory");
                asm volatile("prefetch.tensormap [%0];" :: "l"(&tmWo) : "memory");
                uint32_t due = t_start + T_FIRST;
#pragma unroll 1
                for (int n = W0; n < 32; n++) {
                    wait_until(due);
                    due += T_TILE;
                    if (n >= WINDOW) mbar_wait(bars + BAR_FULL + 8 * tile_slot(n - WINDOW), tile_par(n - WINDOW));
                    const int s = tile_slot(n);
                    if (n == X_SLOT) mbar_wait(bars + BAR_AFREE, 0);
                    if (n >= 13) mbar_wait(bars + BAR_EMPTY + 8 * s, tile_par(n) ^ 1);
                    const uint32_t dst = sb + s * STAGE_BYTES;
                    const uint32_t fb = bars + BAR_FULL + 8 * s;
                    mbar_expect_tx(fb, STAGE_BYTES);
                    if (n < 16) tma3d_hint(dst, &tmK, 0, krow + n * 64, 0, fb, pol);
                    else tma3d_hint(dst, &tmV, 0, pair * 2048 + (n - 16) * 128, r, fb, pol);
                }
                mbar_wait(bars + BAR_EMPTY + 8 * tile_slot(32), tile_par(32) ^ 1);
                mbar_wait(bars + BAR_EMPTY + 8 * tile_slot(33), tile_par(33) ^ 1);
                mbar_wait(bars + BAR_FULL + 8 * tile_slot(27), tile_par(27));
                due = now_ns();
                if ((int)(due - (t_start + T_WO)) < 0) due = t_start + T_WO;
                due += blockIdx.x * T_WO_PIECE / 128;
#pragma unroll
                for (int qd = 0; qd < 4; qd++) {
                    wait_until(due);
                    due += T_WO_PIECE;
                    mbar_expect_tx(bars + BAR_WO + 8 * qd, 8192);
                    tma3d(sb + tile_slot(32 + (qd >> 1)) * STAGE_BYTES + (qd & 1) * 8192, &tmWo,
                          b * 64, r * 64 + qd * 16, hkv * 4, bars + BAR_WO + 8 * qd);
                }
            }
        } else if (warp == 9) {
            mbar_wait(bars + BAR_AFREE, 0);
            const uint4 z = make_uint4(0u, 0u, 0u, 0u);
#pragma unroll 1
            for (int i = 0; i < 4; i++) g_o[(ki * 4 + (b >> 1)) * 256 + (i * 2 + (lane >> 4)) * 32 + (b & 1) * 16 + (lane & 15)] = z;
#pragma unroll 4
            for (int i = 0; i < 16; i++) g_part[(((b * 16 + i) * 4 + (lane >> 3)) * 16 + ki) * 8 + (lane & 7)] = z;
            __syncwarp();
            if (lane == 0) {
                arrive_and_wait(scr->cnt, 128);
                mbar_arrive(bars + BAR_OK);
            }
        }
        __syncwarp();
        asm volatile("barrier.cluster.wait.acquire.aligned;" ::: "memory");
    } else {
        asm volatile("setmaxnreg.inc.sync.aligned.u32 232;");
        const int g = lane >> 2, t = lane & 3;
        const int mi = lane >> 3, r8 = lane & 7;
        mbar_wait(bars + BAR_WQ, 0);

        {
            float acc[4][4];
#pragma unroll
            for (int nt = 0; nt < 4; nt++) { acc[nt][0] = acc[nt][1] = acc[nt][2] = acc[nt][3] = 0.f; }
            const uint32_t wa = sb + SM_A + ((warp >> 1) * 128 + lane) * 64;
            const uint32_t xa = sb + X_SLOT * STAGE_BYTES + (warp >> 1) * 8192 + ((warp & 1) * 16 + (mi & 1) * 8 + r8) * 128;
#pragma unroll 1
            for (int i = 0; i < 4; i++) {
                uint32_t a0[4], a1[4];
                ldsm4(a0, xa + (i >> 1) * 4096 + ((((i & 1) * 4 + (mi >> 1)) ^ r8) << 4));
                ldsm4(a1, xa + (i >> 1) * 4096 + ((((i & 1) * 4 + 2 + (mi >> 1)) ^ r8) << 4));
#pragma unroll
                for (int nt = 0; nt < 4; nt++) {
                    uint32_t bw[4];
                    ldsm4t(bw, wa + i * 2048 + ((nt ^ (r8 >> 1)) << 4));
                    mma16816(acc[nt], a0[0], a0[1], a0[2], a0[3], bw[0], bw[1]);
                    mma16816(acc[nt], a1[0], a1[1], a1[2], a1[3], bw[2], bw[3]);
                }
            }
            float4* red = reinterpret_cast<float4*>(smem + SM_A + 32768);
#pragma unroll
            for (int hf = 0; hf < 2; hf++) {
                const int idx = (warp >> 1) * 256 + ((warp & 1) * 16 + hf * 8 + g) * 4 + t;
                red[idx] = make_float4(acc[0][2 * hf], acc[0][2 * hf + 1], acc[1][2 * hf], acc[1][2 * hf + 1]);
                red[idx + 128] = make_float4(acc[2][2 * hf], acc[2][2 * hf + 1], acc[3][2 * hf], acc[3][2 * hf + 1]);
            }
            bar_compute();
            if (tid < 128) {
                uint32_t w[4];
#pragma unroll
                for (int hf = 0; hf < 2; hf++) {
                    const float4 v0 = red[hf * 128 + tid], v1 = red[256 + hf * 128 + tid], v2 = red[512 + hf * 128 + tid], v3 = red[768 + hf * 128 + tid];
                    w[2 * hf] = nz(pack_bf16((v0.x + v1.x) + (v2.x + v3.x), (v0.y + v1.y) + (v2.y + v3.y)));
                    w[2 * hf + 1] = nz(pack_bf16((v0.z + v1.z) + (v2.z + v3.z), (v0.w + v1.w) + (v2.w + v3.w)));
                }
                st_relaxed_v4(&g_q[(((tid >> 4) * 8 + hkv) * 16 + b * 2 + r) * 16 + (tid & 15)], w);
            }
        }
        uint4 qf[8];
        {
            const uint4* qsrc = &g_q[pair * 256 + tid];
            bar_compute();
            if (tid == 0) mbar_arrive(bars + BAR_AFREE);
            spin_clocks(clock64(), Q_DELAY);
            uint4 w = ld_relaxed_v4(qsrc);
            int it = 0;
            while (!valid4(w)) {
                w = ld_relaxed_v4(qsrc);
                if (++it > SPIN_LIMIT) give_up();
            }
            uint4* qs = reinterpret_cast<uint4*>(smem + SM_A + 49152);
            qs[tid] = w;
            bar_compute();
#pragma unroll
            for (int i = 0; i < 8; i++) qf[i] = qs[((g >> 2) * 4 + (i & 1) * 8 + (i >> 1)) * 16 + (g & 3) * 4 + t];
        }

        uint32_t S[16][2];
#pragma unroll
        for (int i = 0; i < 16; i++) S[i][0] = S[i][1] = 0u;
        {
            const uint32_t ka = sb + (warp * 8 + r8) * 128;
#pragma unroll 1
            for (int n = 0; n < 16; n++) {
#pragma unroll
                for (int i = 0; i < 15; i++) { S[i][0] = S[i + 1][0]; S[i][1] = S[i + 1][1]; }
                const int s = tile_slot(n);
                mbar_wait(bars + BAR_FULL + 8 * s, tile_par(n));
                float e[4] = {0.f, 0.f, 0.f, 0.f}, o[4] = {0.f, 0.f, 0.f, 0.f};
#pragma unroll
                for (int i = 0; i < 4; i++) {
                    uint32_t kf[4];
                    ldsm4(kf, ka + s * STAGE_BYTES + (i >> 1) * 8192 + (((((i & 1) << 2) + mi) ^ r8) << 4));
                    mma16816(e, qf[2 * i].x, qf[2 * i + 1].x, qf[2 * i].y, qf[2 * i + 1].y, kf[0], kf[1]);
                    mma16816(o, qf[2 * i].z, qf[2 * i + 1].z, qf[2 * i].w, qf[2 * i + 1].w, kf[2], kf[3]);
                }
#pragma unroll
                for (int i = 0; i < 2; i++) {
                    const uint32_t d = pack_bf16(e[2 * i] + o[2 * i], e[2 * i + 1] + o[2 * i + 1]);
                    S[15][i] = pack_bf16(bf16_lo(d) * 0.08838834764831845f, bf16_hi(d) * 0.08838834764831845f);
                }
                if (s < NSTAGE) {
                    __syncwarp();
                    if (lane == 0) mbar_arrive(bars + BAR_EMPTY + 8 * s);
                }
            }
        }

        asm volatile("barrier.cluster.wait.acquire.aligned;" ::: "memory");
        uint32_t peer;
        asm("mapa.shared::cluster.u32 %0, %1, %2;" : "=r"(peer) : "r"(sb), "r"(r ^ 1));
        float inv0, inv1;
        {
            uint32_t h0 = S[0][0], h1 = S[0][1];
#pragma unroll
            for (int n = 1; n < 16; n++) { h0 = max_bf16x2(h0, S[n][0]); h1 = max_bf16x2(h1, S[n][1]); }
            float m0 = fmaxf(bf16_lo(h0), bf16_hi(h0)), m1 = fmaxf(bf16_lo(h1), bf16_hi(h1));
            m0 = fmaxf(m0, __shfl_xor_sync(0xffffffffu, m0, 1)); m1 = fmaxf(m1, __shfl_xor_sync(0xffffffffu, m1, 1));
            m0 = fmaxf(m0, __shfl_xor_sync(0xffffffffu, m0, 2)); m1 = fmaxf(m1, __shfl_xor_sync(0xffffffffu, m1, 2));
            const uint32_t off = (uint32_t)(((t & 1) * 8 + g) * 16 + r * 8 + warp) * 4;
            const float mv = (t & 1) ? m1 : m0;
            if (t & 2) asm volatile("st.async.shared::cluster.mbarrier::complete_tx::bytes.f32 [%0], %1, [%2];"
                                    :: "r"(peer + SM_MX + off), "f"(mv), "r"(peer + SM_BAR + BAR_MX) : "memory");
            else asm volatile("st.shared.f32 [%0], %1;" :: "r"(sb + SM_MX + off), "f"(mv) : "memory");
            __syncwarp();
            if (lane == 0) mbar_arrive(bars + BAR_MX);
            mbar_wait_cluster(bars + BAR_MX, 0);
            if (tid < 128) g_q[pair * 256 + r * 128 + tid] = make_uint4(0u, 0u, 0u, 0u);
            const float4* mx = reinterpret_cast<const float4*>(smem + SM_MX);
            const float4 u0 = mx[g * 4 + t], u1 = mx[(g + 8) * 4 + t];
            m0 = fmaxf(fmaxf(u0.x, u0.y), fmaxf(u0.z, u0.w));
            m1 = fmaxf(fmaxf(u1.x, u1.y), fmaxf(u1.z, u1.w));
            m0 = fmaxf(m0, __shfl_xor_sync(0xffffffffu, m0, 1)); m1 = fmaxf(m1, __shfl_xor_sync(0xffffffffu, m1, 1));
            m0 = fmaxf(m0, __shfl_xor_sync(0xffffffffu, m0, 2)); m1 = fmaxf(m1, __shfl_xor_sync(0xffffffffu, m1, 2));
            const float c = 1.4426950408889634f;
            float l0 = 0.f, l1 = 0.f;
            const uint32_t poff = SM_A + (r * 8 + warp) * 4096 + lane * 16;
#pragma unroll 1
            for (int u = 0; u < 8; u++) {
                float p[8];
#pragma unroll
                for (int i = 0; i < 8; i++) {
                    const uint32_t d = S[i >> 2][(i >> 1) & 1];
                    p[i] = ex2((((i & 1) ? bf16_hi(d) : bf16_lo(d)) - ((i & 2) ? m1 : m0)) * c);
                }
                l0 += (p[0] + p[1]) + (p[4] + p[5]);
                l1 += (p[2] + p[3]) + (p[6] + p[7]);
                sts128(sb + poff + u * 512, make_uint4(pack_bf16(p[0], p[1]), pack_bf16(p[2], p[3]), pack_bf16(p[4], p[5]), pack_bf16(p[6], p[7])));
#pragma unroll
                for (int i = 0; i < 14; i++) { S[i][0] = S[i + 2][0]; S[i][1] = S[i + 2][1]; }
            }
            asm volatile("fence.proxy.async.shared::cta;" ::: "memory");
            __syncwarp();
            if (lane == 0)
                asm volatile("cp.async.bulk.shared::cluster.shared::cta.mbarrier::complete_tx::bytes [%0], [%1], %2, [%3];"
                             :: "r"(peer + poff), "r"(sb + poff), "r"(4096), "r"(peer + SM_BAR + BAR_P) : "memory");
            l0 += __shfl_xor_sync(0xffffffffu, l0, 1); l1 += __shfl_xor_sync(0xffffffffu, l1, 1);
            l0 += __shfl_xor_sync(0xffffffffu, l0, 2); l1 += __shfl_xor_sync(0xffffffffu, l1, 2);
            const float lv = (t & 1) ? l1 : l0;
            if (t & 2) asm volatile("st.async.shared::cluster.mbarrier::complete_tx::bytes.f32 [%0], %1, [%2];"
                                    :: "r"(peer + SM_LS + off), "f"(lv), "r"(peer + SM_BAR + BAR_P) : "memory");
            else asm volatile("st.shared.f32 [%0], %1;" :: "r"(sb + SM_LS + off), "f"(lv) : "memory");
            __syncwarp();
            if (lane == 0) mbar_arrive(bars + BAR_P);
            mbar_wait_cluster(bars + BAR_P, 0);
            const float4* ls = reinterpret_cast<const float4*>(smem + SM_LS);
            const float4 v0 = ls[g * 4 + t], v1 = ls[(g + 8) * 4 + t];
            l0 = (v0.x + v0.y) + (v0.z + v0.w);
            l1 = (v1.x + v1.y) + (v1.z + v1.w);
            l0 += __shfl_xor_sync(0xffffffffu, l0, 1); l1 += __shfl_xor_sync(0xffffffffu, l1, 1);
            l0 += __shfl_xor_sync(0xffffffffu, l0, 2); l1 += __shfl_xor_sync(0xffffffffu, l1, 2);
            inv0 = 1.f / l0; inv1 = 1.f / l1;
        }

        const int mp = warp & 1, nt = warp >> 1;
        const int po = nt * 256 + (lane >> 4) * 32 + mp * 16 + (lane & 15);
        uint32_t o_dst_off = offsetof(Scratch, o) + 8 * ((((ki * 4 + (b >> 1)) * 8 + warp) * 32 + ((b & 1) * 4 + (g & 3)) * 4 + t) * 2 + (g >> 2));
        uint32_t o_src_off = offsetof(Scratch, o) + 16 * (ki * 1024 + po);
        uint32_t p_dst_off = offsetof(Scratch, part) + 16 * ((((b * 16 + t) * 4 + (warp & 3)) * 16 + ki) * 8 + g);
        unsigned char* const sc = reinterpret_cast<unsigned char*>(scr);
        uint32_t os_st = sb + tile_slot(O_TILE) * STAGE_BYTES + po * 16;
        uint32_t os_ld = sb + tile_slot(O_TILE) * STAGE_BYTES + lane * 16;
        uint32_t wa0 = sb + (mi >> 1) * 4096 + r8 * 128 + ((((warp & 3) * 2 + (mi & 1)) ^ r8) << 4);
        uint32_t va = sb + ((mi & 1) * 64 + (mi >> 1) * 8 + r8) * 128 + ((warp ^ r8) << 4);
        uint32_t pa = sb + SM_A + lane * 16;
        uint32_t tb = bars;
        asm volatile("" : "+r"(o_dst_off), "+r"(o_src_off), "+r"(p_dst_off));
        asm volatile("" : "+r"(os_st), "+r"(os_ld), "+r"(wa0), "+r"(va), "+r"(pa), "+r"(tb));

        float oa[4][4];
#pragma unroll
        for (int i = 0; i < 4; i++) { oa[i][0] = oa[i][1] = oa[i][2] = oa[i][3] = 0.f; }
        auto pv_tile = [&](int v, int s, uint32_t ph) {
            uint4 p[8];
#pragma unroll
            for (int j = 0; j < 8; j++) p[j] = lds128(pa + ((v >> 3) * 64 + (v & 7)) * 512 + j * 4096);
            const uint32_t vs = va + s * STAGE_BYTES;
            mbar_wait(tb + BAR_FULL + 8 * s, ph);
#pragma unroll
            for (int j2 = 0; j2 < 4; j2++) {
                uint32_t vf[4];
                ldsm4t(vf, vs + j2 * 2048);
                mma16816(oa[(2 * j2) & 3], p[2 * j2].x, p[2 * j2].y, p[2 * j2].z, p[2 * j2].w, vf[0], vf[1]);
                mma16816(oa[(2 * j2 + 1) & 3], p[2 * j2 + 1].x, p[2 * j2 + 1].y, p[2 * j2 + 1].z, p[2 * j2 + 1].w, vf[2], vf[3]);
            }
        };
        {
            int s = tile_slot(16);
            uint32_t ph = tile_par(16);
#pragma unroll 1
            for (int v = 0; v < 15; v++) {
                pv_tile(v, s, ph);
                __syncwarp();
                if (lane == 0) mbar_arrive(tb + BAR_EMPTY + 8 * s);
                if (++s == NSTAGE) { s = 0; ph ^= 1; }
            }
        }
        mbar_wait(tb + BAR_OK, 0);
        mbar_wait(tb + BAR_EMPTY + 8 * tile_slot(O_TILE), tile_par(O_TILE));
        pv_tile(15, tile_slot(31), tile_par(31));
        {
            const float o0 = ((oa[0][0] + oa[1][0]) + (oa[2][0] + oa[3][0])) * inv0;
            const float o1 = ((oa[0][1] + oa[1][1]) + (oa[2][1] + oa[3][1])) * inv0;
            const float o2 = ((oa[0][2] + oa[1][2]) + (oa[2][2] + oa[3][2])) * inv1;
            const float o3 = ((oa[0][3] + oa[1][3]) + (oa[2][3] + oa[3][3])) * inv1;
            asm volatile("red.relaxed.gpu.global.or.b64 [%0], %1;"
                         :: "l"(sc + o_dst_off), "l"((uint64_t)nz(pack_bf16(o0, o1)) | (uint64_t)nz(pack_bf16(o2, o3)) << 32) : "memory");
        }

        {
            spin_clocks(clock64(), O_DELAY);
            const uint4* o_src = reinterpret_cast<const uint4*>(sc + o_src_off);
            uint4 og[4];
#pragma unroll
            for (int j = 0; j < 4; j++) og[j] = ld_relaxed_v4(o_src + j * 64);
            const uint32_t ob = tb + BAR_O + 8 * nt;
            bool done = false;
            int it = 0;
            auto poll = [&]() {
                bool ok = true;
#pragma unroll
                for (int j = 0; j < 4; j++) {
                    if (!valid4(og[j])) { og[j] = ld_relaxed_v4(o_src + j * 64); ok = false; }
                }
                if (__all_sync(0xffffffffu, ok)) {
#pragma unroll
                    for (int j = 0; j < 4; j++) sts128(os_st + j * 1024, og[j]);
                    __syncwarp();
                    if (lane == 0) mbar_arrive(ob);
                    done = true;
                }
            };
            uint32_t wf[4][4][4];
            auto load_wo = [&](int qd) {
#pragma unroll
                for (int k = 0; k < 4; k++)
                    ldsm4t(wf[qd][k], wa0 + tile_slot(32 + (qd >> 1)) * STAGE_BYTES + (qd & 1) * 8192 + (k & 1) * 2048 + (k >> 1) * 1024);
            };
            bool have[4];
#pragma unroll
            for (int qd = 0; qd < 4; qd++) {
                while (true) {
                    have[qd] = mbar_test(tb + BAR_WO + 8 * qd, 0);
                    if (have[qd]) break;
                    if (!done) poll();
                    else if (mbar_test(ob, 0)) break;
                    if (++it > SPIN_LIMIT) give_up();
                }
                if (have[qd]) load_wo(qd);
            }
            while (!done) {
                poll();
                if (++it > SPIN_LIMIT) give_up();
            }
            int rt = nt;
            while (!mbar_test(tb + BAR_O + 8 * rt, 0)) {
                rt ^= 1;
                if (++it > SPIN_LIMIT) give_up();
            }
            auto row_tile = [&](bool first) {
                uint4 of[8];
#pragma unroll
                for (int w = 0; w < 8; w++) of[w] = lds128(os_ld + rt * 4096 + w * 512);
                float acc[4][4];
#pragma unroll
                for (int i = 0; i < 16; i++) acc[i >> 2][i & 3] = 0.f;
#pragma unroll
                for (int qd = 0; qd < 4; qd++) {
                    if (first && !have[qd]) {
                        mbar_wait(tb + BAR_WO + 8 * qd, 0);
                        load_wo(qd);
                    }
#pragma unroll
                    for (int k = 0; k < 4; k++) {
                        const uint4& o4 = of[qd * 2 + (k >> 1)];
                        mma16816(acc[k], wf[qd][k][0], wf[qd][k][1], wf[qd][k][2], wf[qd][k][3], (k & 1) ? o4.z : o4.x, (k & 1) ? o4.w : o4.y);
                    }
                }
                uint32_t w[4];
#pragma unroll
                for (int i = 0; i < 4; i++) w[i] = nz(__float_as_uint((acc[0][i] + acc[1][i]) + (acc[2][i] + acc[3][i])));
                st_relaxed_v4(sc + p_dst_off + rt * 32768, w);
            };
            row_tile(true);
            rt ^= 1;
            mbar_wait(tb + BAR_O + 8 * rt, 0);
            row_tile(false);
        }

        if (mp == 0) {
            const long long t0 = clock64();
            const uint4* p_src = &g_part[((b * 16 + ki) * 4 + nt) * 128 + lane];
            __nv_bfloat16* out_dst = out + (2 * ki + (mi & 1)) * 512 + b * 64 + nt * 16 + r8 + (mi >> 1) * 8;
            asm volatile("" : "+l"(p_src), "+l"(out_dst));
            spin_clocks(t0, PART_DELAY);
            uint4 u[4];
#pragma unroll
            for (int j = 0; j < 4; j++) u[j] = ld_relaxed_v4(p_src + j * 32);
            int it = 0;
            while (true) {
                bool ok = true;
#pragma unroll
                for (int j = 0; j < 4; j++) {
                    if (!valid4(u[j])) { u[j] = ld_relaxed_v4(p_src + j * 32); ok = false; }
                }
                if (__all_sync(0xffffffffu, ok)) break;
                if (++it > SPIN_LIMIT) give_up();
            }
            float v0 = (__uint_as_float(u[0].x) + __uint_as_float(u[1].x)) + (__uint_as_float(u[2].x) + __uint_as_float(u[3].x));
            float v1 = (__uint_as_float(u[0].y) + __uint_as_float(u[1].y)) + (__uint_as_float(u[2].y) + __uint_as_float(u[3].y));
            float v2 = (__uint_as_float(u[0].z) + __uint_as_float(u[1].z)) + (__uint_as_float(u[2].z) + __uint_as_float(u[3].z));
            float v3 = (__uint_as_float(u[0].w) + __uint_as_float(u[1].w)) + (__uint_as_float(u[2].w) + __uint_as_float(u[3].w));
#pragma unroll
            for (int d = 8; d < 32; d <<= 1) {
                v0 += __shfl_xor_sync(0xffffffffu, v0, d);
                v1 += __shfl_xor_sync(0xffffffffu, v1, d);
                v2 += __shfl_xor_sync(0xffffffffu, v2, d);
                v3 += __shfl_xor_sync(0xffffffffu, v3, d);
            }
            *out_dst = __float2bfloat16_rn((mi & 2) ? ((mi & 1) ? v3 : v2) : ((mi & 1) ? v1 : v0));
        }
    }
}

typedef CUresult (*EncodeTiledFn)(CUtensorMap*, CUtensorMapDataType, cuuint32_t, void*, const cuuint64_t*, const cuuint64_t*,
                                  const cuuint32_t*, const cuuint32_t*, CUtensorMapInterleave, CUtensorMapSwizzle,
                                  CUtensorMapL2promotion, CUtensorMapFloatOOBfill);

void encode3d(EncodeTiledFn enc, CUtensorMap* tm, const void* base, cuuint64_t d0, cuuint64_t d1, cuuint64_t d2,
              cuuint64_t s1, cuuint64_t s2, cuuint32_t b0, cuuint32_t b1, cuuint32_t b2,
              CUtensorMapSwizzle sw = CU_TENSOR_MAP_SWIZZLE_128B,
              CUtensorMapL2promotion promo = CU_TENSOR_MAP_L2_PROMOTION_L2_256B) {
    const cuuint64_t dims[3] = {d0, d1, d2};
    const cuuint64_t strides[2] = {s1, s2};
    const cuuint32_t box[3] = {b0, b1, b2};
    const cuuint32_t es[3] = {1, 1, 1};
    enc(tm, CU_TENSOR_MAP_DATA_TYPE_BFLOAT16, 3, const_cast<void*>(base), dims, strides, box, es,
        CU_TENSOR_MAP_INTERLEAVE_NONE, sw, promo, CU_TENSOR_MAP_FLOAT_OOB_FILL_NONE);
}

}

extern "C" void kernel_launch(void* const* d_in, const int* in_sizes, int n_in, void* d_out, int out_size) {
    (void)in_sizes; (void)n_in; (void)out_size;
    const __nv_bfloat16* x = (const __nv_bfloat16*)d_in[0];
    const __nv_bfloat16* kc = (const __nv_bfloat16*)d_in[1];
    const __nv_bfloat16* vc = (const __nv_bfloat16*)d_in[2];
    const __nv_bfloat16* wq = (const __nv_bfloat16*)d_in[3];
    const __nv_bfloat16* wo = (const __nv_bfloat16*)d_in[4];

    static EncodeTiledFn enc = nullptr;
    static Scratch* scr = nullptr;
    if (!enc) {
        cudaGetSymbolAddress((void**)&scr, g_scratch);
        void* fn = nullptr;
        cudaDriverEntryPointQueryResult st;
        cudaGetDriverEntryPoint("cuTensorMapEncodeTiled", &fn, cudaEnableDefault, &st);
        enc = (EncodeTiledFn)fn;
        cudaFuncSetAttribute(gqa_fused_kernel, cudaFuncAttributeMaxDynamicSharedMemorySize, SM_TOTAL);
    }
    CUtensorMap tmK, tmV, tmWo, tmWq, tmX;
    encode3d(enc, &tmK, kc, 64, 131072, 2, 256, 128, 64, 64, 2);
    encode3d(enc, &tmV, vc, 64, 131072, 2, 256, 128, 64, 128, 1);
    encode3d(enc, &tmWo, wo, 512, 128, 32, 1024, 131072, 64, 16, 4, CU_TENSOR_MAP_SWIZZLE_128B, CU_TENSOR_MAP_L2_PROMOTION_NONE);
    encode3d(enc, &tmWq, wq, 4096, 256, 2, 8192, 256 * 8192, 32, 256, 2, CU_TENSOR_MAP_SWIZZLE_64B);
    encode3d(enc, &tmX, x, 64, 32, 8, 1024, 128, 64, 32, 8);
    gqa_fused_kernel<<<128, NTHREADS, SM_TOTAL, cudaStreamPerThread>>>(wq, x, (__nv_bfloat16*)d_out, scr, tmK, tmV, tmWo, tmWq, tmX);
}
```

```cpp
#include <cuda_runtime.h>
#include <cuda.h>
#include <cuda_bf16.h>
#include <stdint.h>
#include <stddef.h>

namespace {

constexpr int NSTAGE = 10;
constexpr int STAGE_BYTES = 16384;
constexpr int NTHREADS = 320;

constexpr int W0 = 2;
constexpr uint32_t T_FIRST = 1400;
constexpr uint32_t T_SKEW = 200;
constexpr uint32_t T_TILE = 640;
constexpr int WINDOW = 8;
constexpr uint32_t T_WO = 21830;
constexpr uint32_t T_WO_PIECE = 350;
constexpr int Q_DELAY = 4000;
constexpr int O_DELAY = 300;
constexpr int PART_DELAY = 300;

constexpr int SM_A = NSTAGE * STAGE_BYTES;
constexpr int SM_BAR = SM_A + 65536;
constexpr int SM_MX = SM_BAR + 320;
constexpr int SM_LS = SM_MX + 1024;
constexpr int SM_TOTAL = SM_LS + 1024;

constexpr int BAR_FULL = 0;
constexpr int BAR_EMPTY = BAR_FULL + 8 * 13;
constexpr int BAR_WO = BAR_EMPTY + 8 * NSTAGE;
constexpr int BAR_MX = BAR_WO + 32;
constexpr int BAR_P = BAR_MX + 8;
constexpr int BAR_OK = BAR_P + 8;
constexpr int BAR_WQ = BAR_OK + 8;
constexpr int BAR_AFREE = BAR_WQ + 8;
constexpr int BAR_O = BAR_AFREE + 8;
constexpr int BAR_END = BAR_O + 32;
static_assert(BAR_END <= 320, "barrier area");

__host__ __device__ constexpr int tile_seq(int n) { return n < 10 ? n : n - 3; }
__host__ __device__ constexpr int tile_slot(int n) { return (n >= 10 && n < 13) ? n : tile_seq(n) % NSTAGE; }
__host__ __device__ constexpr int tile_par(int n) { return (n >= 10 && n < 13) ? 0 : (tile_seq(n) / NSTAGE) & 1; }
constexpr int X_SLOT = 8;
constexpr int O_TILE = 24;

constexpr int SPIN_LIMIT = 1 << 20;

struct Scratch {
    uint4 q[64 * 16 * 16];
    uint4 o[16 * 4 * 8 * 32];
    uint4 part[8 * 16 * 4 * 16 * 8];
    unsigned int cnt[32];
};
__device__ Scratch g_scratch;

__device__ __forceinline__ uint32_t smem_u32(const void* p) { return (uint32_t)__cvta_generic_to_shared(p); }
__device__ __forceinline__ void give_up() {
    asm volatile("st.volatile.global.u32 [%0], %1;\n\texit;" :: "l"(0ull), "r"(0) : "memory");
}
__device__ __forceinline__ uint32_t now_ns() {
    uint32_t t;
    asm volatile("mov.u32 %0, %%globaltimer_lo;" : "=r"(t));
    return t;
}
__device__ __forceinline__ void wait_until(uint32_t due) {
    for (int i = 0; i < (1 << 16) && (int)(now_ns() - due) < 0; i++) {}
}
__device__ __forceinline__ void spin_clocks(long long t0, int n) { while (clock64() - t0 < n) {} }
__device__ __forceinline__ void mbar_init(uint32_t bar, uint32_t count) {
    asm volatile("mbarrier.init.shared::cta.b64 [%0], %1;" :: "r"(bar), "r"(count) : "memory");
}
__device__ __forceinline__ void mbar_expect_tx(uint32_t bar, uint32_t bytes) {
    asm volatile("mbarrier.arrive.expect_tx.shared::cta.b64 _, [%0], %1;" :: "r"(bar), "r"(bytes) : "memory");
}
__device__ __forceinline__ void mbar_arrive(uint32_t bar) {
    asm volatile("mbarrier.arrive.shared::cta.b64 _, [%0];" :: "r"(bar) : "memory");
}
__device__ __forceinline__ void mbar_wait(uint32_t bar, uint32_t parity) {
    uint32_t ok;
    int it = 0;
    do {
        asm volatile("{\n.reg .pred p;\nmbarrier.try_wait.parity.shared::cta.b64 p, [%1], %2;\nselp.u32 %0, 1, 0, p;\n}"
                     : "=r"(ok) : "r"(bar), "r"(parity) : "memory");
        if (++it > SPIN_LIMIT) give_up();
    } while (!ok);
}
__device__ __forceinline__ bool mbar_test(uint32_t bar, uint32_t parity) {
    uint32_t ok;
    asm volatile("{\n.reg .pred p;\nmbarrier.test_wait.parity.shared::cta.b64 p, [%1], %2;\nselp.u32 %0, 1, 0, p;\n}"
                 : "=r"(ok) : "r"(bar), "r"(parity) : "memory");
    return __all_sync(0xffffffffu, ok != 0);
}
__device__ __forceinline__ void mbar_wait_cluster(uint32_t bar, uint32_t parity) {
    uint32_t ok;
    int it = 0;
    do {
        asm volatile("{\n.reg .pred p;\nmbarrier.try_wait.parity.acquire.cluster.shared::cta.b64 p, [%1], %2;\nselp.u32 %0, 1, 0, p;\n}"
                     : "=r"(ok) : "r"(bar), "r"(parity) : "memory");
        if (++it > SPIN_LIMIT) give_up();
    } while (!ok);
}
__device__ __forceinline__ void tma3d(uint32_t dst, const CUtensorMap* tm, int c0, int c1, int c2, uint32_t bar) {
    asm volatile("cp.async.bulk.tensor.3d.shared::cluster.global.mbarrier::complete_tx::bytes [%0], [%1, {%3, %4, %5}], [%2];"
                 :: "r"(dst), "l"(tm), "r"(bar), "r"(c0), "r"(c1), "r"(c2) : "memory");
}
__device__ __forceinline__ void tma3d_hint(uint32_t dst, const CUtensorMap* tm, int c0, int c1, int c2, uint32_t bar, uint64_t pol) {
    asm volatile("cp.async.bulk.tensor.3d.shared::cluster.global.mbarrier::complete_tx::bytes.L2::cache_hint [%0], [%1, {%3, %4, %5}], [%2], %6;"
                 :: "r"(dst), "l"(tm), "r"(bar), "r"(c0), "r"(c1), "r"(c2), "l"(pol) : "memory");
}
__device__ __forceinline__ void ldsm4(uint32_t (&r)[4], uint32_t addr) {
    asm volatile("ldmatrix.sync.aligned.m8n8.x4.shared.b16 {%0, %1, %2, %3}, [%4];"
                 : "=r"(r[0]), "=r"(r[1]), "=r"(r[2]), "=r"(r[3]) : "r"(addr) : "memory");
}
__device__ __forceinline__ void ldsm4t(uint32_t (&r)[4], uint32_t addr) {
    asm volatile("ldmatrix.sync.aligned.m8n8.x4.trans.shared.b16 {%0, %1, %2, %3}, [%4];"
                 : "=r"(r[0]), "=r"(r[1]), "=r"(r[2]), "=r"(r[3]) : "r"(addr) : "memory");
}
__device__ __forceinline__ void mma16816(float (&c)[4], uint32_t a0, uint32_t a1, uint32_t a2, uint32_t a3, uint32_t b0, uint32_t b1) {
    asm volatile("mma.sync.aligned.m16n8k16.row.col.f32.bf16.bf16.f32 {%0, %1, %2, %3}, {%4, %5, %6, %7}, {%8, %9}, {%0, %1, %2, %3};"
                 : "+f"(c[0]), "+f"(c[1]), "+f"(c[2]), "+f"(c[3]) : "r"(a0), "r"(a1), "r"(a2), "r"(a3), "r"(b0), "r"(b1));
}
__device__ __forceinline__ uint32_t pack_bf16(float lo, float hi) {
    uint32_t r;
    asm("cvt.rn.bf16x2.f32 %0, %1, %2;" : "=r"(r) : "f"(hi), "f"(lo));
    return r;
}
__device__ __forceinline__ float bf16_lo(uint32_t d) { return __uint_as_float(d << 16); }
__device__ __forceinline__ float bf16_hi(uint32_t d) { return __uint_as_float(d & 0xffff0000u); }
__device__ __forceinline__ uint32_t max_bf16x2(uint32_t a, uint32_t b) {
    uint32_t r;
    asm("max.bf16x2 %0, %1, %2;" : "=r"(r) : "r"(a), "r"(b));
    return r;
}
__device__ __forceinline__ float ex2(float x) {
    float r;
    asm("ex2.approx.ftz.f32 %0, %1;" : "=f"(r) : "f"(x));
    return r;
}
__device__ __forceinline__ uint4 ld_relaxed_v4(const uint4* p) {
    uint4 v;
    asm volatile("ld.relaxed.gpu.global.v4.u32 {%0, %1, %2, %3}, [%4];" : "=r"(v.x), "=r"(v.y), "=r"(v.z), "=r"(v.w) : "l"(p) : "memory");
    return v;
}
__device__ __forceinline__ void st_relaxed_v4(void* p, const uint32_t (&w)[4]) {
    asm volatile("st.relaxed.gpu.global.v4.u32 [%0], {%1, %2, %3, %4};" :: "l"(p), "r"(w[0]), "r"(w[1]), "r"(w[2]), "r"(w[3]) : "memory");
}
__device__ __forceinline__ uint4 lds128(uint32_t a) {
    uint4 v;
    asm volatile("ld.shared.v4.u32 {%0, %1, %2, %3}, [%4];" : "=r"(v.x), "=r"(v.y), "=r"(v.z), "=r"(v.w) : "r"(a) : "memory");
    return v;
}
__device__ __forceinline__ void sts128(uint32_t a, const uint4& v) {
    asm volatile("st.shared.v4.u32 [%0], {%1, %2, %3, %4};" :: "r"(a), "r"(v.x), "r"(v.y), "r"(v.z), "r"(v.w) : "memory");
}
__device__ __forceinline__ uint32_t nz(uint32_t w) { return w == 0u ? 0x80000000u : w; }
__device__ __forceinline__ bool valid4(const uint4& v) { return v.x != 0u && v.y != 0u && v.z != 0u && v.w != 0u; }
__device__ __forceinline__ void bar_compute() { asm volatile("bar.sync 1, 256;" ::: "memory"); }

__device__ __forceinline__ void arrive_and_wait(unsigned int* cnt, unsigned int n) {
    unsigned int old;
    asm volatile("atom.add.release.gpu.global.u32 %0, [%1], 1;" : "=r"(old) : "l"(cnt) : "memory");
    const unsigned int target = (old | (n - 1)) + 1;
    unsigned int cur;
    int it = 0;
    do {
        asm volatile("ld.acquire.gpu.global.u32 %0, [%1];" : "=r"(cur) : "l"(cnt) : "memory");
        if (++it > SPIN_LIMIT) give_up();
    } while ((int)(cur - target) < 0);
}

__global__ void __cluster_dims__(2, 1, 1) __launch_bounds__(NTHREADS, 1)
gqa_fused_kernel(const __nv_bfloat16* __restrict__ wq, const __nv_bfloat16* __restrict__ x, __nv_bfloat16* __restrict__ out,
                 Scratch* __restrict__ scr,
                 const __grid_constant__ CUtensorMap tmK, const __grid_constant__ CUtensorMap tmV,
                 const __grid_constant__ CUtensorMap tmWo, const __grid_constant__ CUtensorMap tmWq,
                 const __grid_constant__ CUtensorMap tmX) {
    extern __shared__ __align__(1024) unsigned char smem[];
    const int tid = threadIdx.x;
    uint4* const g_q = scr->q;
    uint4* const g_o = scr->o;
    uint4* const g_part = scr->part;
    const uint32_t sb = smem_u32(smem);
    const uint32_t bars = sb + SM_BAR;
    const int warp = tid >> 5, lane = tid & 31;
    const int r = blockIdx.x & 1;
    const int pair = blockIdx.x >> 1;
    const int b = pair >> 3, hkv = pair & 7;
    const int krow = blockIdx.x * 1024;
    uint64_t pol;
    asm volatile("createpolicy.fractional.L2::evict_first.b64 %0, 1.0;" : "=l"(pol));
    const uint32_t t_start = now_ns();

    if (tid == 0) {
        asm volatile("cp.async.bulk.prefetch.L2.global [%0], %1;" :: "l"(x + blockIdx.x * 128), "r"(256) : "memory");
        asm volatile("cp.async.bulk.prefetch.L2.global [%0], %1;" :: "l"(wq + blockIdx.x * 16384), "r"(32768) : "memory");
        mbar_init(bars + BAR_WQ, 1);
#pragma unroll
        for (int n = 0; n < W0; n++) mbar_init(bars + BAR_FULL + 8 * n, 1);
        asm volatile("fence.proxy.async.shared::cta;" ::: "memory");
        mbar_expect_tx(bars + BAR_WQ, 65536);
        tma3d(sb + X_SLOT * STAGE_BYTES, &tmX, 0, 0, 0, bars + BAR_WQ);
        tma3d(sb + SM_A, &tmWq, hkv * 512 + (b * 2 + r) * 32, 0, 0, bars + BAR_WQ);
#pragma unroll
        for (int n = 0; n < W0; n++) {
            mbar_expect_tx(bars + BAR_FULL + 8 * n, STAGE_BYTES);
            tma3d_hint(sb + n * STAGE_BYTES, &tmK, 0, krow + n * 64, 0, bars + BAR_FULL + 8 * n, pol);
        }
#pragma unroll
        for (int off = 8 * W0; off < BAR_END; off += 8)
            if (off != BAR_WQ)
                mbar_init(bars + off, off < BAR_EMPTY ? 1 : off < BAR_WO ? 8 : off < BAR_MX ? 1 : off < BAR_OK ? 9 : off >= BAR_O ? 2 : 1);
        mbar_expect_tx(bars + BAR_MX, 512);
        mbar_expect_tx(bars + BAR_P, 32768 + 512);
        asm volatile("fence.mbarrier_init.release.cluster;" ::: "memory");
        asm volatile("fence.proxy.async.shared::cta;" ::: "memory");
    }
    __syncwarp();
    asm volatile("barrier.cluster.arrive.relaxed.aligned;" ::: "memory");
    __syncthreads();

    const int ki = hkv * 2 + r;
    if (__shfl_sync(0xffffffffu, tid >> 7, 0) == 2) {
        if (warp == 8) {
            if (lane == 0) {
                asm volatile("prefetch.tensormap [%0];" :: "l"(&tmV) : "memory");
                asm volatile("prefetch.tensormap [%0];" :: "l"(&tmWo) : "memory");
                uint32_t due = t_start + T_FIRST + blockIdx.x * T_SKEW / 128;
#pragma unroll 1
                for (int n = W0; n < 32; n++) {
                    wait_until(due);
                    due += T_TILE;
                    if (n >= WINDOW) mbar_wait(bars + BAR_FULL + 8 * tile_slot(n - WINDOW), tile_par(n - WINDOW));
                    const int s = tile_slot(n);
                    if (n == X_SLOT) mbar_wait(bars + BAR_AFREE, 0);
                    if (n >= 13) mbar_wait(bars + BAR_EMPTY + 8 * s, tile_par(n) ^ 1);
                    const uint32_t dst = sb + s * STAGE_BYTES;
                    const uint32_t fb = bars + BAR_FULL + 8 * s;
                    mbar_expect_tx(fb, STAGE_BYTES);
                    if (n < 16) tma3d_hint(dst, &tmK, 0, krow + n * 64, 0, fb, pol);
                    else tma3d_hint(dst, &tmV, 0, pair * 2048 + (n - 16) * 128, r, fb, pol);
                }
                mbar_wait(bars + BAR_EMPTY + 8 * tile_slot(32), tile_par(32) ^ 1);
                mbar_wait(bars + BAR_EMPTY + 8 * tile_slot(33), tile_par(33) ^ 1);
                mbar_wait(bars + BAR_FULL + 8 * tile_slot(27), tile_par(27));
                due = now_ns();
                if ((int)(due - (t_start + T_WO)) < 0) due = t_start + T_WO;
                due += blockIdx.x * T_WO_PIECE / 128;
#pragma unroll
                for (int qd = 0; qd < 4; qd++) {
                    wait_until(due);
                    due += T_WO_PIECE;
                    mbar_expect_tx(bars + BAR_WO + 8 * qd, 8192);
                    tma3d(sb + tile_slot(32 + (qd >> 1)) * STAGE_BYTES + (qd & 1) * 8192, &tmWo,
                          b * 64, r * 64 + qd * 16, hkv * 4, bars + BAR_WO + 8 * qd);
                }
            }
        } else {
            mbar_wait(bars + BAR_AFREE, 0);
            const uint4 z = make_uint4(0u, 0u, 0u, 0u);
#pragma unroll 1
            for (int i = 0; i < 4; i++) g_o[(ki * 4 + (b >> 1)) * 256 + (i * 2 + (lane >> 4)) * 32 + (b & 1) * 16 + (lane & 15)] = z;
#pragma unroll 4
            for (int i = 0; i < 16; i++) g_part[(((b * 16 + i) * 4 + (lane >> 3)) * 16 + ki) * 8 + (lane & 7)] = z;
            __syncwarp();
            if (lane == 0) {
                arrive_and_wait(scr->cnt, 128);
                mbar_arrive(bars + BAR_OK);
            }
        }
        __syncwarp();
        asm volatile("barrier.cluster.wait.acquire.aligned;" ::: "memory");
    } else {
        const int g = lane >> 2, t = lane & 3;
        const int mi = lane >> 3, r8 = lane & 7;
        mbar_wait(bars + BAR_WQ, 0);

        {
            float acc[4][4];
#pragma unroll
            for (int nt = 0; nt < 4; nt++) { acc[nt][0] = acc[nt][1] = acc[nt][2] = acc[nt][3] = 0.f; }
            const uint32_t wa = sb + SM_A + ((warp >> 1) * 128 + lane) * 64;
            const uint32_t xa = sb + X_SLOT * STAGE_BYTES + (warp >> 1) * 8192 + ((warp & 1) * 16 + (mi & 1) * 8 + r8) * 128;
#pragma unroll 1
            for (int i = 0; i < 4; i++) {
                uint32_t a0[4], a1[4];
                ldsm4(a0, xa + (i >> 1) * 4096 + ((((i & 1) * 4 + (mi >> 1)) ^ r8) << 4));
                ldsm4(a1, xa + (i >> 1) * 4096 + ((((i & 1) * 4 + 2 + (mi >> 1)) ^ r8) << 4));
#pragma unroll
                for (int nt = 0; nt < 4; nt++) {
                    uint32_t bw[4];
                    ldsm4t(bw, wa + i * 2048 + ((nt ^ (r8 >> 1)) << 4));
                    mma16816(acc[nt], a0[0], a0[1], a0[2], a0[3], bw[0], bw[1]);
                    mma16816(acc[nt], a1[0], a1[1], a1[2], a1[3], bw[2], bw[3]);
                }
            }
            float4* red = reinterpret_cast<float4*>(smem + SM_A + 32768);
#pragma unroll
            for (int hf = 0; hf < 2; hf++) {
                const int idx = (warp >> 1) * 256 + ((warp & 1) * 16 + hf * 8 + g) * 4 + t;
                red[idx] = make_float4(acc[0][2 * hf], acc[0][2 * hf + 1], acc[1][2 * hf], acc[1][2 * hf + 1]);
                red[idx + 128] = make_float4(acc[2][2 * hf], acc[2][2 * hf + 1], acc[3][2 * hf], acc[3][2 * hf + 1]);
            }
            bar_compute();
            if (tid < 128) {
                uint32_t w[4];
#pragma unroll
                for (int hf = 0; hf < 2; hf++) {
                    const float4 v0 = red[hf * 128 + tid], v1 = red[256 + hf * 128 + tid], v2 = red[512 + hf * 128 + tid], v3 = red[768 + hf * 128 + tid];
                    w[2 * hf] = nz(pack_bf16((v0.x + v1.x) + (v2.x + v3.x), (v0.y + v1.y) + (v2.y + v3.y)));
                    w[2 * hf + 1] = nz(pack_bf16((v0.z + v1.z) + (v2.z + v3.z), (v0.w + v1.w) + (v2.w + v3.w)));
                }
                st_relaxed_v4(&g_q[(((tid >> 4) * 8 + hkv) * 16 + b * 2 + r) * 16 + (tid & 15)], w);
            }
        }
        uint4 qf[8];
        {
            const uint4* qsrc = &g_q[pair * 256 + tid];
            bar_compute();
            if (tid == 0) mbar_arrive(bars + BAR_AFREE);
            spin_clocks(clock64(), Q_DELAY);
            uint4 w = ld_relaxed_v4(qsrc);
            int it = 0;
            while (!valid4(w)) {
                w = ld_relaxed_v4(qsrc);
                if (++it > SPIN_LIMIT) give_up();
            }
            uint4* qs = reinterpret_cast<uint4*>(smem + SM_A + 49152);
            qs[tid] = w;
            bar_compute();
#pragma unroll
            for (int i = 0; i < 8; i++) qf[i] = qs[((g >> 2) * 4 + (i & 1) * 8 + (i >> 1)) * 16 + (g & 3) * 4 + t];
        }

        uint32_t S[16][2];
#pragma unroll
        for (int i = 0; i < 16; i++) S[i][0] = S[i][1] = 0u;
        {
            const uint32_t ka = sb + (warp * 8 + r8) * 128;
#pragma unroll 1
            for (int n = 0; n < 16; n++) {
#pragma unroll
                for (int i = 0; i < 15; i++) { S[i][0] = S[i + 1][0]; S[i][1] = S[i + 1][1]; }
                const int s = tile_slot(n);
                mbar_wait(bars + BAR_FULL + 8 * s, tile_par(n));
                float e[4] = {0.f, 0.f, 0.f, 0.f}, o[4] = {0.f, 0.f, 0.f, 0.f};
#pragma unroll
                for (int i = 0; i < 4; i++) {
                    uint32_t kf[4];
                    ldsm4(kf, ka + s * STAGE_BYTES + (i >> 1) * 8192 + (((((i & 1) << 2) + mi) ^ r8) << 4));
                    mma16816(e, qf[2 * i].x, qf[2 * i + 1].x, qf[2 * i].y, qf[2 * i + 1].y, kf[0], kf[1]);
                    mma16816(o, qf[2 * i].z, qf[2 * i + 1].z, qf[2 * i].w, qf[2 * i + 1].w, kf[2], kf[3]);
                }
#pragma unroll
                for (int i = 0; i < 2; i++) {
                    const uint32_t d = pack_bf16(e[2 * i] + o[2 * i], e[2 * i + 1] + o[2 * i + 1]);
                    S[15][i] = pack_bf16(bf16_lo(d) * 0.08838834764831845f, bf16_hi(d) * 0.08838834764831845f);
                }
                if (s < NSTAGE) {
                    __syncwarp();
                    if (lane == 0) mbar_arrive(bars + BAR_EMPTY + 8 * s);
                }
            }
        }

        asm volatile("barrier.cluster.wait.acquire.aligned;" ::: "memory");
        uint32_t peer;
        asm("mapa.shared::cluster.u32 %0, %1, %2;" : "=r"(peer) : "r"(sb), "r"(r ^ 1));
        float inv0, inv1;
        {
            uint32_t h0 = S[0][0], h1 = S[0][1];
#pragma unroll
            for (int n = 1; n < 16; n++) { h0 = max_bf16x2(h0, S[n][0]); h1 = max_bf16x2(h1, S[n][1]); }
            float m0 = fmaxf(bf16_lo(h0), bf16_hi(h0)), m1 = fmaxf(bf16_lo(h1), bf16_hi(h1));
            m0 = fmaxf(m0, __shfl_xor_sync(0xffffffffu, m0, 1)); m1 = fmaxf(m1, __shfl_xor_sync(0xffffffffu, m1, 1));
            m0 = fmaxf(m0, __shfl_xor_sync(0xffffffffu, m0, 2)); m1 = fmaxf(m1, __shfl_xor_sync(0xffffffffu, m1, 2));
            const uint32_t off = (uint32_t)(((t & 1) * 8 + g) * 16 + r * 8 + warp) * 4;
            const float mv = (t & 1) ? m1 : m0;
            if (t & 2) asm volatile("st.async.shared::cluster.mbarrier::complete_tx::bytes.f32 [%0], %1, [%2];"
                                    :: "r"(peer + SM_MX + off), "f"(mv), "r"(peer + SM_BAR + BAR_MX) : "memory");
            else asm volatile("st.shared.f32 [%0], %1;" :: "r"(sb + SM_MX + off), "f"(mv) : "memory");
            __syncwarp();
            if (lane == 0) mbar_arrive(bars + BAR_MX);
            mbar_wait_cluster(bars + BAR_MX, 0);
            if (tid < 128) g_q[pair * 256 + r * 128 + tid] = make_uint4(0u, 0u, 0u, 0u);
            const float4* mx = reinterpret_cast<const float4*>(smem + SM_MX);
            const float4 u0 = mx[g * 4 + t], u1 = mx[(g + 8) * 4 + t];
            m0 = fmaxf(fmaxf(u0.x, u0.y), fmaxf(u0.z, u0.w));
            m1 = fmaxf(fmaxf(u1.x, u1.y), fmaxf(u1.z, u1.w));
            m0 = fmaxf(m0, __shfl_xor_sync(0xffffffffu, m0, 1)); m1 = fmaxf(m1, __shfl_xor_sync(0xffffffffu, m1, 1));
            m0 = fmaxf(m0, __shfl_xor_sync(0xffffffffu, m0, 2)); m1 = fmaxf(m1, __shfl_xor_sync(0xffffffffu, m1, 2));
            const float c = 1.4426950408889634f;
            float l0 = 0.f, l1 = 0.f;
            const uint32_t poff = SM_A + (r * 8 + warp) * 4096 + lane * 16;
#pragma unroll 1
            for (int u = 0; u < 8; u++) {
                float p[8];
#pragma unroll
                for (int i = 0; i < 8; i++) {
                    const uint32_t d = S[i >> 2][(i >> 1) & 1];
                    p[i] = ex2((((i & 1) ? bf16_hi(d) : bf16_lo(d)) - ((i & 2) ? m1 : m0)) * c);
                }
                l0 += (p[0] + p[1]) + (p[4] + p[5]);
                l1 += (p[2] + p[3]) + (p[6] + p[7]);
                sts128(sb + poff + u * 512, make_uint4(pack_bf16(p[0], p[1]), pack_bf16(p[2], p[3]), pack_bf16(p[4], p[5]), pack_bf16(p[6], p[7])));
#pragma unroll
                for (int i = 0; i < 14; i++) { S[i][0] = S[i + 2][0]; S[i][1] = S[i + 2][1]; }
            }
            asm volatile("fence.proxy.async.shared::cta;" ::: "memory");
            __syncwarp();
            if (lane == 0)
                asm volatile("cp.async.bulk.shared::cluster.shared::cta.mbarrier::complete_tx::bytes [%0], [%1], %2, [%3];"
                             :: "r"(peer + poff), "r"(sb + poff), "r"(4096), "r"(peer + SM_BAR + BAR_P) : "memory");
            l0 += __shfl_xor_sync(0xffffffffu, l0, 1); l1 += __shfl_xor_sync(0xffffffffu, l1, 1);
            l0 += __shfl_xor_sync(0xffffffffu, l0, 2); l1 += __shfl_xor_sync(0xffffffffu, l1, 2);
            const float lv = (t & 1) ? l1 : l0;
            if (t & 2) asm volatile("st.async.shared::cluster.mbarrier::complete_tx::bytes.f32 [%0], %1, [%2];"
                                    :: "r"(peer + SM_LS + off), "f"(lv), "r"(peer + SM_BAR + BAR_P) : "memory");
            else asm volatile("st.shared.f32 [%0], %1;" :: "r"(sb + SM_LS + off), "f"(lv) : "memory");
            __syncwarp();
            if (lane == 0) mbar_arrive(bars + BAR_P);
            mbar_wait_cluster(bars + BAR_P, 0);
            const float4* ls = reinterpret_cast<const float4*>(smem + SM_LS);
            const float4 v0 = ls[g * 4 + t], v1 = ls[(g + 8) * 4 + t];
            l0 = (v0.x + v0.y) + (v0.z + v0.w);
            l1 = (v1.x + v1.y) + (v1.z + v1.w);
            l0 += __shfl_xor_sync(0xffffffffu, l0, 1); l1 += __shfl_xor_sync(0xffffffffu, l1, 1);
            l0 += __shfl_xor_sync(0xffffffffu, l0, 2); l1 += __shfl_xor_sync(0xffffffffu, l1, 2);
            inv0 = 1.f / l0; inv1 = 1.f / l1;
        }

        const int mp = warp & 1, nt = warp >> 1;
        const int po = nt * 256 + (lane >> 4) * 32 + mp * 16 + (lane & 15);
        uint32_t o_dst_off = offsetof(Scratch, o) + 8 * ((((ki * 4 + (b >> 1)) * 8 + warp) * 32 + ((b & 1) * 4 + (g & 3)) * 4 + t) * 2 + (g >> 2));
        uint32_t o_src_off = offsetof(Scratch, o) + 16 * (ki * 1024 + po);
        uint32_t p_dst_off = offsetof(Scratch, part) + 16 * ((((b * 16 + t) * 4 + (warp & 3)) * 16 + ki) * 8 + g);
        unsigned char* const sc = reinterpret_cast<unsigned char*>(scr);
        uint32_t os_st = sb + tile_slot(O_TILE) * STAGE_BYTES + po * 16;
        uint32_t os_ld = sb + tile_slot(O_TILE) * STAGE_BYTES + lane * 16;
        uint32_t wa0 = sb + (mi >> 1) * 4096 + r8 * 128 + ((((warp & 3) * 2 + (mi & 1)) ^ r8) << 4);
        uint32_t va = sb + ((mi & 1) * 64 + (mi >> 1) * 8 + r8) * 128 + ((warp ^ r8) << 4);
        uint32_t pa = sb + SM_A + lane * 16;
        uint32_t tb = bars;
        asm volatile("" : "+r"(o_dst_off), "+r"(o_src_off), "+r"(p_dst_off));
        asm volatile("" : "+r"(os_st), "+r"(os_ld), "+r"(wa0), "+r"(va), "+r"(pa), "+r"(tb));

        float oa[4][4];
#pragma unroll
        for (int i = 0; i < 4; i++) { oa[i][0] = oa[i][1] = oa[i][2] = oa[i][3] = 0.f; }
        auto pv_tile = [&](int v, int s, uint32_t ph) {
            uint4 p[8];
#pragma unroll
            for (int j = 0; j < 8; j++) p[j] = lds128(pa + ((v >> 3) * 64 + (v & 7)) * 512 + j * 4096);
            const uint32_t vs = va + s * STAGE_BYTES;
            mbar_wait(tb + BAR_FULL + 8 * s, ph);
#pragma unroll
            for (int j2 = 0; j2 < 4; j2++) {
                uint32_t vf[4];
                ldsm4t(vf, vs + j2 * 2048);
                mma16816(oa[(2 * j2) & 3], p[2 * j2].x, p[2 * j2].y, p[2 * j2].z, p[2 * j2].w, vf[0], vf[1]);
                mma16816(oa[(2 * j2 + 1) & 3], p[2 * j2 + 1].x, p[2 * j2 + 1].y, p[2 * j2 + 1].z, p[2 * j2 + 1].w, vf[2], vf[3]);
            }
        };
        {
            int s = tile_slot(16);
            uint32_t ph = tile_par(16);
#pragma unroll 1
            for (int v = 0; v < 15; v++) {
                pv_tile(v, s, ph);
                __syncwarp();
                if (lane == 0) mbar_arrive(tb + BAR_EMPTY + 8 * s);
                if (++s == NSTAGE) { s = 0; ph ^= 1; }
            }
        }
        mbar_wait(tb + BAR_OK, 0);
        mbar_wait(tb + BAR_EMPTY + 8 * tile_slot(O_TILE), tile_par(O_TILE));
        pv_tile(15, tile_slot(31), tile_par(31));
        {
            const float o0 = ((oa[0][0] + oa[1][0]) + (oa[2][0] + oa[3][0])) * inv0;
            const float o1 = ((oa[0][1] + oa[1][1]) + (oa[2][1] + oa[3][1])) * inv0;
            const float o2 = ((oa[0][2] + oa[1][2]) + (oa[2][2] + oa[3][2])) * inv1;
            const float o3 = ((oa[0][3] + oa[1][3]) + (oa[2][3] + oa[3][3])) * inv1;
            asm volatile("red.relaxed.gpu.global.or.b64 [%0], %1;"
                         :: "l"(sc + o_dst_off), "l"((uint64_t)nz(pack_bf16(o0, o1)) | (uint64_t)nz(pack_bf16(o2, o3)) << 32) : "memory");
        }

        {
            spin_clocks(clock64(), O_DELAY);
            const uint4* o_src = reinterpret_cast<const uint4*>(sc + o_src_off);
            uint4 og[4];
#pragma unroll
            for (int j = 0; j < 4; j++) og[j] = ld_relaxed_v4(o_src + j * 64);
            const uint32_t ob = tb + BAR_O + 8 * nt;
            bool done = false;
            int it = 0;
            auto poll = [&]() {
                bool ok = true;
#pragma unroll
                for (int j = 0; j < 4; j++) {
                    if (!valid4(og[j])) { og[j] = ld_relaxed_v4(o_src + j * 64); ok = false; }
                }
                if (__all_sync(0xffffffffu, ok)) {
#pragma unroll
                    for (int j = 0; j < 4; j++) sts128(os_st + j * 1024, og[j]);
                    __syncwarp();
                    if (lane == 0) mbar_arrive(ob);
                    done = true;
                }
            };
            uint32_t wf[4][4][4];
            auto load_wo = [&](int qd) {
#pragma unroll
                for (int k = 0; k < 4; k++)
                    ldsm4t(wf[qd][k], wa0 + tile_slot(32 + (qd >> 1)) * STAGE_BYTES + (qd & 1) * 8192 + (k & 1) * 2048 + (k >> 1) * 1024);
            };
            bool have[4];
#pragma unroll
            for (int qd = 0; qd < 4; qd++) {
                while (true) {
                    have[qd] = mbar_test(tb + BAR_WO + 8 * qd, 0);
                    if (have[qd]) break;
                    if (!done) poll();
                    else if (mbar_test(ob, 0)) break;
                    if (++it > SPIN_LIMIT) give_up();
                }
                if (have[qd]) load_wo(qd);
            }
            while (!done) {
                poll();
                if (++it > SPIN_LIMIT) give_up();
            }
            int rt = nt;
            while (!mbar_test(tb + BAR_O + 8 * rt, 0)) {
                rt ^= 1;
                if (++it > SPIN_LIMIT) give_up();
            }
            auto row_tile = [&](bool first) {
                uint4 of[8];
#pragma unroll
                for (int w = 0; w < 8; w++) of[w] = lds128(os_ld + rt * 4096 + w * 512);
                float acc[4][4];
#pragma unroll
                for (int i = 0; i < 16; i++) acc[i >> 2][i & 3] = 0.f;
#pragma unroll
                for (int qd = 0; qd < 4; qd++) {
                    if (first && !have[qd]) {
                        mbar_wait(tb + BAR_WO + 8 * qd, 0);
                        load_wo(qd);
                    }
#pragma unroll
                    for (int k = 0; k < 4; k++) {
                        const uint4& o4 = of[qd * 2 + (k >> 1)];
                        mma16816(acc[k], wf[qd][k][0], wf[qd][k][1], wf[qd][k][2], wf[qd][k][3], (k & 1) ? o4.z : o4.x, (k & 1) ? o4.w : o4.y);
                    }
                }
                uint32_t w[4];
#pragma unroll
                for (int i = 0; i < 4; i++) w[i] = nz(__float_as_uint((acc[0][i] + acc[1][i]) + (acc[2][i] + acc[3][i])));
                st_relaxed_v4(sc + p_dst_off + rt * 32768, w);
            };
            row_tile(true);
            rt ^= 1;
            mbar_wait(tb + BAR_O + 8 * rt, 0);
            row_tile(false);
        }

        if (mp == 0) {
            const long long t0 = clock64();
            const uint4* p_src = &g_part[((b * 16 + ki) * 4 + nt) * 128 + lane];
            __nv_bfloat16* out_dst = out + (2 * ki + (mi & 1)) * 512 + b * 64 + nt * 16 + r8 + (mi >> 1) * 8;
            asm volatile("" : "+l"(p_src), "+l"(out_dst));
            spin_clocks(t0, PART_DELAY);
            uint4 u[4];
#pragma unroll
            for (int j = 0; j < 4; j++) u[j] = ld_relaxed_v4(p_src + j * 32);
            int it = 0;
            while (true) {
                bool ok = true;
#pragma unroll
                for (int j = 0; j < 4; j++) {
                    if (!valid4(u[j])) { u[j] = ld_relaxed_v4(p_src + j * 32); ok = false; }
                }
                if (__all_sync(0xffffffffu, ok)) break;
                if (++it > SPIN_LIMIT) give_up();
            }
            float v0 = (__uint_as_float(u[0].x) + __uint_as_float(u[1].x)) + (__uint_as_float(u[2].x) + __uint_as_float(u[3].x));
            float v1 = (__uint_as_float(u[0].y) + __uint_as_float(u[1].y)) + (__uint_as_float(u[2].y) + __uint_as_float(u[3].y));
            float v2 = (__uint_as_float(u[0].z) + __uint_as_float(u[1].z)) + (__uint_as_float(u[2].z) + __uint_as_float(u[3].z));
            float v3 = (__uint_as_float(u[0].w) + __uint_as_float(u[1].w)) + (__uint_as_float(u[2].w) + __uint_as_float(u[3].w));
#pragma unroll
            for (int d = 8; d < 32; d <<= 1) {
                v0 += __shfl_xor_sync(0xffffffffu, v0, d);
                v1 += __shfl_xor_sync(0xffffffffu, v1, d);
                v2 += __shfl_xor_sync(0xffffffffu, v2, d);
                v3 += __shfl_xor_sync(0xffffffffu, v3, d);
            }
            *out_dst = __float2bfloat16_rn((mi & 2) ? ((mi & 1) ? v3 : v2) : ((mi & 1) ? v1 : v0));
        }
    }
}

typedef CUresult (*EncodeTiledFn)(CUtensorMap*, CUtensorMapDataType, cuuint32_t, void*, const cuuint64_t*, const cuuint64_t*,
                                  const cuuint32_t*, const cuuint32_t*, CUtensorMapInterleave, CUtensorMapSwizzle,
                                  CUtensorMapL2promotion, CUtensorMapFloatOOBfill);

void encode3d(EncodeTiledFn enc, CUtensorMap* tm, const void* base, cuuint64_t d0, cuuint64_t d1, cuuint64_t d2,
              cuuint64_t s1, cuuint64_t s2, cuuint32_t b0, cuuint32_t b1, cuuint32_t b2,
              CUtensorMapSwizzle sw = CU_TENSOR_MAP_SWIZZLE_128B,
              CUtensorMapL2promotion promo = CU_TENSOR_MAP_L2_PROMOTION_L2_256B) {
    const cuuint64_t dims[3] = {d0, d1, d2};
    const cuuint64_t strides[2] = {s1, s2};
    const cuuint32_t box[3] = {b0, b1, b2};
    const cuuint32_t es[3] = {1, 1, 1};
    enc(tm, CU_TENSOR_MAP_DATA_TYPE_BFLOAT16, 3, const_cast<void*>(base), dims, strides, box, es,
        CU_TENSOR_MAP_INTERLEAVE_NONE, sw, promo, CU_TENSOR_MAP_FLOAT_OOB_FILL_NONE);
}

}

extern "C" void kernel_launch(void* const* d_in, const int* in_sizes, int n_in, void* d_out, int out_size) {
    (void)in_sizes; (void)n_in; (void)out_size;
    const __nv_bfloat16* x = (const __nv_bfloat16*)d_in[0];
    const __nv_bfloat16* kc = (const __nv_bfloat16*)d_in[1];
    const __nv_bfloat16* vc = (const __nv_bfloat16*)d_in[2];
    const __nv_bfloat16* wq = (const __nv_bfloat16*)d_in[3];
    const __nv_bfloat16* wo = (const __nv_bfloat16*)d_in[4];

    static EncodeTiledFn enc = nullptr;
    static Scratch* scr = nullptr;
    if (!enc) {
        cudaGetSymbolAddress((void**)&scr, g_scratch);
        void* fn = nullptr;
        cudaDriverEntryPointQueryResult st;
        cudaGetDriverEntryPoint("cuTensorMapEncodeTiled", &fn, cudaEnableDefault, &st);
        enc = (EncodeTiledFn)fn;
        cudaFuncSetAttribute(gqa_fused_kernel, cudaFuncAttributeMaxDynamicSharedMemorySize, SM_TOTAL);
    }
    CUtensorMap tmK, tmV, tmWo, tmWq, tmX;
    encode3d(enc, &tmK, kc, 64, 131072, 2, 256, 128, 64, 64, 2);
    encode3d(enc, &tmV, vc, 64, 131072, 2, 256, 128, 64, 128, 1);
    encode3d(enc, &tmWo, wo, 512, 128, 32, 1024, 131072, 64, 16, 4, CU_TENSOR_MAP_SWIZZLE_128B, CU_TENSOR_MAP_L2_PROMOTION_NONE);
    encode3d(enc, &tmWq, wq, 4096, 256, 2, 8192, 256 * 8192, 32, 256, 2, CU_TENSOR_MAP_SWIZZLE_64B);
    encode3d(enc, &tmX, x, 64, 32, 8, 1024, 128, 64, 32, 8);
    gqa_fused_kernel<<<128, NTHREADS, SM_TOTAL, cudaStreamPerThread>>>(wq, x, (__nv_bfloat16*)d_out, scr, tmK, tmV, tmWo, tmWq, tmX);
}
```
